```python
import torch

def _softmax(x, axis=-1):
    return torch.softmax(x, dim=axis)
def _gelu(x):
    return torch.nn.functional.gelu(x, approximate="tanh")
def _silu(x):
    return torch.nn.functional.silu(x)
def _sigmoid(x):
    return torch.sigmoid(x)
def _layernorm(x, axis=-1, eps=1e-5):
    m = x.mean(dim=axis, keepdim=True)
    v = x.var(dim=axis, keepdim=True, unbiased=False)
    return (x - m) / torch.sqrt(v + eps)
def _scatter_add(tgt, idx, src, axis=0):
    return tgt.clone().index_add_(axis, idx, src)
def _segment_sum(src, seg, n):
    out = torch.zeros((n,) + src.shape[1:], dtype=src.dtype)
    return out.index_add_(0, seg, src)
def _pad(x, pw):
    flat = tuple(v for pair in reversed(pw) for v in pair)
    return torch.nn.functional.pad(x, flat)

kernel_name = 'concat_heads__linear_kernel_hedgehog__ssm_conv_s5__prompt'

def setup_inputs():

    _w = (lambda a: (lambda t: t.to(torch.bfloat16) if t.is_floating_point() else t)(torch.as_tensor(a)))
    def _A_setup():
        B, S, D, H = 1, 2048, 640, 32
        Dh = D // H
        return {
            "x": _w((lambda *s: torch.randn(*s, dtype=torch.bfloat16) * 0.4)(B, S, D)),
            "wqkv": _w((lambda *s: torch.randn(*s, dtype=torch.bfloat16) * 0.4)(D, 3 * D)),
            "w_phi": _w((lambda *s: torch.randn(*s, dtype=torch.bfloat16) * 0.4)(H, Dh, Dh) * (Dh ** -0.5)),
            "wo": _w((lambda *s: torch.randn(*s, dtype=torch.bfloat16) * 0.05)(D, D)),
        }
    _A_in = _A_setup()

    def _B_setup():
        B, S, D = 1, 2048, 640
        P = D
        Lambda_re = -0.5 * (lambda _x: torch.exp(torch.as_tensor(_x)))((lambda *s: torch.randn(*s, dtype=torch.bfloat16) * 0.8)(P))
        Lambda_im = (lambda *s: torch.randn(*s, dtype=torch.bfloat16) * 0.8)(P) * 1.0
        B_re = (lambda *s: torch.randn(*s, dtype=torch.bfloat16) * 0.8)(P, D) * (D ** -0.5)
        B_im = (lambda *s: torch.randn(*s, dtype=torch.bfloat16) * 0.8)(P, D) * (D ** -0.5)
        C_re = (lambda *s: torch.randn(*s, dtype=torch.bfloat16) * 0.8)(D, P) * (P ** -0.5)
        C_im = (lambda *s: torch.randn(*s, dtype=torch.bfloat16) * 0.8)(D, P) * (P ** -0.5)
        log_dt = (lambda *s: torch.randn(*s, dtype=torch.bfloat16) * 0.8)(P) * 0.3 - 2.0
        Dskip = (lambda *s: torch.randn(*s, dtype=torch.bfloat16) * 0.8)(D)
        return {
            "x": _w((lambda *s: torch.randn(*s, dtype=torch.bfloat16) * 0.05)(B, S, D)),
            "Lambda_re": _w(Lambda_re),
            "Lambda_im": _w(Lambda_im),
            "B_re": _w(B_re),
            "B_im": _w(B_im),
            "C_re": _w(C_re),
            "C_im": _w(C_im),
            "log_dt": _w(log_dt),
            "Dskip": _w(Dskip),
        }
    _B_in = _B_setup()

    return {
        "A_x": _A_in["x"],
        "A_wqkv": _A_in["wqkv"],
        "A_w_phi": _A_in["w_phi"],
        "A_wo": _A_in["wo"],
        "B_x": _B_in["x"],
        "B_Lambda_re": _B_in["Lambda_re"],
        "B_Lambda_im": _B_in["Lambda_im"],
        "B_B_re": _B_in["B_re"],
        "B_B_im": _B_in["B_im"],
        "B_C_re": _B_in["C_re"],
        "B_C_im": _B_in["C_im"],
        "B_log_dt": _B_in["log_dt"],
        "B_Dskip": _B_in["Dskip"],
    }

def reference(A_x, A_wqkv, A_w_phi, A_wo, B_x, B_Lambda_re, B_Lambda_im, B_B_re, B_B_im, B_C_re, B_C_im, B_log_dt, B_Dskip):
    def _A_ref(x, wqkv, w_phi, wo):
        B, S, D = x.shape
        H = 32; Dh = D // H
        qkv = (lambda x, *d: x.permute(*d))((x @ wqkv).reshape(B, S, 3, H, Dh), 2, 0, 3, 1, 4)
        q, k, v = qkv[0], qkv[1], qkv[2]
        pq = torch.einsum("bhsd,hdf->bhsf", q, w_phi)
        pk = torch.einsum("bhsd,hdf->bhsf", k, w_phi)
        phi_q = torch.concatenate([_softmax(pq, axis=-1), _softmax(-pq, axis=-1)], axis=-1)
        phi_k = torch.concatenate([_softmax(pk, axis=-1), _softmax(-pk, axis=-1)], axis=-1)
        kv = torch.einsum("bhsf,bhsd->bhfd", phi_k, v)
        z  = torch.einsum("bhsf->bhf", phi_k)
        num = torch.einsum("bhqf,bhfd->bhqd", phi_q, kv)
        den = torch.einsum("bhqf,bhf->bhq", phi_q, z)[..., None] + 1e-6
        o = num / den
        return (lambda x, *d: x.permute(*d))(o, 0, 2, 1, 3).reshape(B, S, D) @ wo

    def _B_ref(x, Lambda_re, Lambda_im, B_re, B_im, C_re, C_im, log_dt, Dskip):
        Bsz, L, H = x.shape
        Lam = Lambda_re + 1j * Lambda_im
        Bmat = B_re + 1j * B_im
        Cmat = C_re + 1j * C_im
        dt = torch.exp(log_dt)
        Lam_bar = torch.exp(dt * Lam)
        B_bar = ((Lam_bar - 1.0) / Lam)[:, None] * Bmat
        Bu = torch.einsum("bld,pd->blp", x + 0j, B_bar)
        h = torch.zeros_like(Bu[:, 0, :])
        hs = []
        for t in range(L):
            h = Lam_bar[None, :] * h + Bu[:, t, :]
            hs.append(h)
        hseq = torch.stack(hs, 1)
        y = 2.0 * torch.einsum("blp,dp->bld", hseq, Cmat).real + x * Dskip[None, None, :]
        return y

    a = _A_ref(A_x, A_wqkv, A_w_phi, A_wo)
    b = _B_ref(B_x, B_Lambda_re, B_Lambda_im, B_B_re, B_B_im, B_C_re, B_C_im, B_log_dt, B_Dskip)
    return torch.concatenate([a, b], axis=-1)
```

```cpp
#include <cuda_runtime.h>
#include <cuda_bf16.h>
#include <cuda.h>
#include <stdint.h>

typedef __nv_bfloat16 bf16;

struct alignas(64) Params {
    CUtensorMap xa, wv, wo, xb, bm, cre, cim, out;
    const bf16 *wqkv, *wphi, *xbp, *lre, *lim, *ldt, *dskip;
    int swap;
};

__device__ uint4 g_wp[2 * 4 * 80 * 20 * 8];
__device__ float4 g_kv[2][32 * 240];
__device__ uint4 g_o[16 * 8 * 1280];
__device__ uint4 g_h[16 * 20 * 1024];
__device__ uint4 g_agg[16 * 640];
__device__ uint32_t g_wflag[2 * 4 * 16];
__device__ uint32_t g_kvflag[4 * 16];
__device__ uint32_t g_oflag[16 * 16];
__device__ uint32_t g_hflag[16 * 5 * 4];
__device__ uint32_t g_epoch_a = 1, g_epoch_b = 1;
#define PROF_T(i)
#define PROF_W(i)

constexpr uint32_t SM_RING = 163840;
constexpr uint32_t SM_BAR = 231424;
constexpr uint32_t SM_TOTAL = 232448;
constexpr uint32_t A_STG = SM_RING + 30720;
constexpr uint32_t A_KVB = 0, A_OWN = 30 * 1024, A_WO = 70 * 1024, A_OB = 145 * 1024;
enum { AB_XF = 0, AB_WF = 10, AB_WE = 16, AB_SF = 22, AB_SE = 24, AB_XFREE = 26, AB_KVB = 27, AB_QDONE = 28,
       AB_WOF = 29, AB_WOE = 33, AB_OF = 37, AB_OWNFREE = 43, AB_OST = 45, AB_N = 49 };
enum { BB_XF = 0, BB_WF = 10, BB_WE = 18, BB_TURN = 26, BB_HF = 29, BB_HE = 35, BB_CF = 41, BB_CE = 47, BB_N = 53 };

__device__ __forceinline__ void mbar_init(uint32_t bar, uint32_t cnt) {
    asm volatile("mbarrier.init.shared::cta.b64 [%0], %1;" ::"r"(bar), "r"(cnt) : "memory");
}
__device__ __forceinline__ void mbar_expect(uint32_t bar, uint32_t bytes) {
    asm volatile("mbarrier.arrive.expect_tx.shared::cta.b64 _, [%0], %1;" ::"r"(bar), "r"(bytes) : "memory");
}
__device__ __forceinline__ void mbar_arrive(uint32_t bar, uint32_t cnt = 1) {
    asm volatile("mbarrier.arrive.shared::cta.b64 _, [%0], %1;" ::"r"(bar), "r"(cnt) : "memory");
}
__device__ __forceinline__ uint32_t mapa(uint32_t addr, uint32_t cta) {
    uint32_t r;
    asm("mapa.shared::cluster.u32 %0, %1, %2;" : "=r"(r) : "r"(addr), "r"(cta));
    return r;
}
__device__ __forceinline__ void mbar_arrive_cl(uint32_t bar_cl, uint32_t cnt = 1) {
    asm volatile("mbarrier.arrive.shared::cluster.b64 _, [%0], %1;" ::"r"(bar_cl), "r"(cnt) : "memory");
}
__device__ __forceinline__ void mbar_expect_cl(uint32_t bar_cl, uint32_t bytes) {
    asm volatile("mbarrier.arrive.expect_tx.shared::cluster.b64 _, [%0], %1;" ::"r"(bar_cl), "r"(bytes) : "memory");
}
__device__ __forceinline__ void mbar_wait(uint32_t bar, uint32_t parity) {
    asm volatile(
        "{\n.reg .pred p;\n.reg .u32 n;\nmov.u32 n, 0;\n"
        "WAIT_LOOP:\n"
        "mbarrier.try_wait.parity.shared::cta.b64 p, [%0], %1;\n"
        "@p bra WAIT_DONE;\n"
        "add.u32 n, n, 1;\n"
        "setp.lt.u32 p, n, 0x400000;\n"
        "@p bra WAIT_LOOP;\n"
        "trap;\n"
        "WAIT_DONE:\n}" ::"r"(bar), "r"(parity) : "memory");
}
__device__ __forceinline__ void bar_sync(int id, int n) { asm volatile("bar.sync %0, %1;" ::"r"(id), "r"(n) : "memory"); }
__device__ __forceinline__ void bar_arrive(int id, int n) { asm volatile("bar.arrive %0, %1;" ::"r"(id), "r"(n) : "memory"); }
__device__ __forceinline__ void fence_async_smem() { asm volatile("fence.proxy.async.shared::cta;" ::: "memory"); }
__device__ __forceinline__ void fence_gpu() { asm volatile("fence.acq_rel.gpu;" ::: "memory"); }
__device__ __forceinline__ void st_flag(uint32_t* p, uint32_t v) {
    asm volatile("st.relaxed.gpu.global.u32 [%0], %1;" ::"l"(p), "r"(v) : "memory");
}
__device__ __forceinline__ uint32_t ld_flag(const uint32_t* p) {
    uint32_t v;
    asm volatile("ld.relaxed.gpu.global.u32 %0, [%1];" : "=r"(v) : "l"(p) : "memory");
    return v;
}
__device__ __forceinline__ void poll_flags(const uint32_t* p, bool active, uint32_t tag) {
#pragma unroll 1
    for (int it = 0; it < (1 << 22); it++) {
        bool ok = !active || ld_flag(p) == tag;
        if (__all_sync(0xffffffffu, ok)) return;
    }
    __trap();
}
__device__ __forceinline__ void tma2d(uint32_t dst, const CUtensorMap* m, int c0, int c1, uint32_t bar) {
    asm volatile("cp.async.bulk.tensor.2d.shared::cluster.global.mbarrier::complete_tx::bytes [%0], [%1, {%3, %4}], [%2];"
                 ::"r"(dst), "l"(m), "r"(bar), "r"(c0), "r"(c1) : "memory");
}
__device__ __forceinline__ void tma4d(uint32_t dst, const CUtensorMap* m, int c0, int c1, int c2, int c3, uint32_t bar) {
    asm volatile("cp.async.bulk.tensor.4d.shared::cluster.global.mbarrier::complete_tx::bytes [%0], [%1, {%3, %4, %5, %6}], [%2];"
                 ::"r"(dst), "l"(m), "r"(bar), "r"(c0), "r"(c1), "r"(c2), "r"(c3) : "memory");
}
__device__ __forceinline__ void tma2d_mc(uint32_t dst, const CUtensorMap* m, int c0, int c1, uint32_t bar) {
    asm volatile("cp.async.bulk.tensor.2d.shared::cluster.global.mbarrier::complete_tx::bytes.multicast::cluster [%0], [%1, {%3, %4}], [%2], %5;"
                 ::"r"(dst), "l"(m), "r"(bar), "r"(c0), "r"(c1), "h"((uint16_t)3) : "memory");
}
__device__ __forceinline__ void tma3d_mc(uint32_t dst, const CUtensorMap* m, int c0, int c1, int c2, uint32_t bar) {
    asm volatile("cp.async.bulk.tensor.3d.shared::cluster.global.mbarrier::complete_tx::bytes.multicast::cluster [%0], [%1, {%3, %4, %5}], [%2], %6;"
                 ::"r"(dst), "l"(m), "r"(bar), "r"(c0), "r"(c1), "r"(c2), "h"((uint16_t)3) : "memory");
}
__device__ __forceinline__ void tma4d_mc(uint32_t dst, const CUtensorMap* m, int c0, int c1, int c2, int c3, uint32_t bar) {
    asm volatile("cp.async.bulk.tensor.4d.shared::cluster.global.mbarrier::complete_tx::bytes.multicast::cluster [%0], [%1, {%3, %4, %5, %6}], [%2], %7;"
                 ::"r"(dst), "l"(m), "r"(bar), "r"(c0), "r"(c1), "r"(c2), "r"(c3), "h"((uint16_t)3) : "memory");
}
__device__ __forceinline__ void bulk_ld(uint32_t dst, const void* src, uint32_t bytes, uint32_t bar) {
    asm volatile("cp.async.bulk.shared::cluster.global.mbarrier::complete_tx::bytes [%0], [%1], %2, [%3];"
                 ::"r"(dst), "l"(src), "r"(bytes), "r"(bar) : "memory");
}
__device__ __forceinline__ void bulk_ld_mc(uint32_t dst, const void* src, uint32_t bytes, uint32_t bar) {
    asm volatile("cp.async.bulk.shared::cluster.global.mbarrier::complete_tx::bytes.multicast::cluster [%0], [%1], %2, [%3], %4;"
                 ::"r"(dst), "l"(src), "r"(bytes), "r"(bar), "h"((uint16_t)3) : "memory");
}
__device__ __forceinline__ void bulk_st(void* dst, uint32_t src, uint32_t bytes) {
    asm volatile("cp.async.bulk.global.shared::cta.bulk_group [%0], [%1], %2;" ::"l"(dst), "r"(src), "r"(bytes) : "memory");
}
__device__ __forceinline__ void tma2d_st(const CUtensorMap* m, uint32_t src, int c0, int c1) {
    asm volatile("cp.async.bulk.tensor.2d.global.shared::cta.bulk_group [%0, {%2, %3}], [%1];"
                 ::"l"(m), "r"(src), "r"(c0), "r"(c1) : "memory");
}
__device__ __forceinline__ void bulk_commit() { asm volatile("cp.async.bulk.commit_group;" ::: "memory"); }
__device__ __forceinline__ void bulk_prefetch(const void* src, uint32_t bytes) {
    asm volatile("cp.async.bulk.prefetch.L2.global [%0], %1;" ::"l"(src), "r"(bytes) : "memory");
}
__device__ __forceinline__ void wg_fence() { asm volatile("wgmma.fence.sync.aligned;" ::: "memory"); }
__device__ __forceinline__ void wg_commit() { asm volatile("wgmma.commit_group.sync.aligned;" ::: "memory"); }
template <int N> __device__ __forceinline__ void wg_wait() { asm volatile("wgmma.wait_group.sync.aligned %0;" ::"n"(N) : "memory"); }
template <int N> __device__ __forceinline__ void reg_fence(float* d) {
#pragma unroll
    for (int i = 0; i < N; i++) asm volatile("" : "+f"(d[i])::"memory");
}
template <int N> __device__ __forceinline__ void reg_fence(uint32_t* d) {
#pragma unroll
    for (int i = 0; i < N; i++) asm volatile("" : "+r"(d[i])::"memory");
}
template <int N> __device__ __forceinline__ void reg_kill(float* d) {
#pragma unroll
    for (int i = 0; i < N; i++) asm volatile("" : "=f"(d[i])::"memory");
}
__device__ __forceinline__ uint64_t mkdesc(uint32_t addr, uint32_t lbo, uint32_t sbo, uint32_t sw) {
    uint32_t lo = ((addr & 0x3FFFF) >> 4) | ((lbo >> 4) << 16);
    uint32_t hi = (sbo >> 4) | (sw << 30);
    return ((uint64_t)hi << 32) | lo;
}
__device__ __forceinline__ uint32_t pack_bf16(float lo, float hi) {
    uint32_t r;
    asm("cvt.rn.bf16x2.f32 %0, %1, %2;" : "=r"(r) : "f"(hi), "f"(lo));
    return r;
}
__device__ __forceinline__ float ex2(float x) { float r; asm("ex2.approx.ftz.f32 %0, %1;" : "=f"(r) : "f"(x)); return r; }
__device__ __forceinline__ float rcp(float x) { float r; asm("rcp.approx.ftz.f32 %0, %1;" : "=f"(r) : "f"(x)); return r; }
__device__ __forceinline__ void sts128(uint32_t a, uint32_t x, uint32_t y, uint32_t z, uint32_t w) {
    asm volatile("st.shared.v4.u32 [%0], {%1, %2, %3, %4};" ::"r"(a), "r"(x), "r"(y), "r"(z), "r"(w) : "memory");
}
__device__ __forceinline__ void stsm4(uint32_t a, uint32_t x, uint32_t y, uint32_t z, uint32_t w) {
    asm volatile("stmatrix.sync.aligned.m8n8.x4.shared.b16 [%0], {%1, %2, %3, %4};" ::"r"(a), "r"(x), "r"(y), "r"(z), "r"(w) : "memory");
}
__device__ __forceinline__ void stsm2(uint32_t a, uint32_t x, uint32_t y) {
    asm volatile("stmatrix.sync.aligned.m8n8.x2.shared.b16 [%0], {%1, %2};" ::"r"(a), "r"(x), "r"(y) : "memory");
}
__device__ __forceinline__ float4 ldcg4(const float4* p) {
    float4 v;
    asm volatile("ld.global.cg.v4.f32 {%0, %1, %2, %3}, [%4];" : "=f"(v.x), "=f"(v.y), "=f"(v.z), "=f"(v.w) : "l"(p) : "memory");
    return v;
}
template <int N> __device__ __forceinline__ void reg_inc() { asm volatile("setmaxnreg.inc.sync.aligned.u32 %0;" ::"n"(N)); }
template <int N> __device__ __forceinline__ void reg_dec() { asm volatile("setmaxnreg.dec.sync.aligned.u32 %0;" ::"n"(N)); }

template <int TA, int TB>
__device__ __forceinline__ void wgmma_ss_n24(float* d, uint64_t da, uint64_t db, int sd) {
    asm volatile("{\n.reg .pred p;\nsetp.ne.b32 p, %14, 0;\n"
                 "wgmma.mma_async.sync.aligned.m64n24k16.f32.bf16.bf16 {%0, %1, %2, %3, %4, %5, %6, %7, %8, %9, %10, %11}, %12, %13, p, 1, 1, %15, %16;\n}\n"
                 : "+f"(d[0]), "+f"(d[1]), "+f"(d[2]), "+f"(d[3]), "+f"(d[4]), "+f"(d[5]), "+f"(d[6]), "+f"(d[7]), "+f"(d[8]), "+f"(d[9]), "+f"(d[10]), "+f"(d[11])
                 : "l"(da), "l"(db), "r"(sd), "n"(TA), "n"(TB));
}
template <int TA, int TB>
__device__ __forceinline__ void wgmma_ss_n128(float* d, uint64_t da, uint64_t db, int sd) {
    asm volatile("{\n.reg .pred p;\nsetp.ne.b32 p, %66, 0;\n"
                 "wgmma.mma_async.sync.aligned.m64n128k16.f32.bf16.bf16 {%0, %1, %2, %3, %4, %5, %6, %7, %8, %9, %10, %11, %12, %13, %14, %15, %16, %17, %18, %19, %20, %21, %22, %23, %24, %25, %26, %27, %28, %29, %30, %31, %32, %33, %34, %35, %36, %37, %38, %39, %40, %41, %42, %43, %44, %45, %46, %47, %48, %49, %50, %51, %52, %53, %54, %55, %56, %57, %58, %59, %60, %61, %62, %63}, %64, %65, p, 1, 1, %67, %68;\n}\n"
                 : "+f"(d[0]), "+f"(d[1]), "+f"(d[2]), "+f"(d[3]), "+f"(d[4]), "+f"(d[5]), "+f"(d[6]), "+f"(d[7]), "+f"(d[8]), "+f"(d[9]), "+f"(d[10]), "+f"(d[11]), "+f"(d[12]), "+f"(d[13]), "+f"(d[14]), "+f"(d[15]), "+f"(d[16]), "+f"(d[17]), "+f"(d[18]), "+f"(d[19]), "+f"(d[20]), "+f"(d[21]), "+f"(d[22]), "+f"(d[23]), "+f"(d[24]), "+f"(d[25]), "+f"(d[26]), "+f"(d[27]), "+f"(d[28]), "+f"(d[29]), "+f"(d[30]), "+f"(d[31]), "+f"(d[32]), "+f"(d[33]), "+f"(d[34]), "+f"(d[35]), "+f"(d[36]), "+f"(d[37]), "+f"(d[38]), "+f"(d[39]), "+f"(d[40]), "+f"(d[41]), "+f"(d[42]), "+f"(d[43]), "+f"(d[44]), "+f"(d[45]), "+f"(d[46]), "+f"(d[47]), "+f"(d[48]), "+f"(d[49]), "+f"(d[50]), "+f"(d[51]), "+f"(d[52]), "+f"(d[53]), "+f"(d[54]), "+f"(d[55]), "+f"(d[56]), "+f"(d[57]), "+f"(d[58]), "+f"(d[59]), "+f"(d[60]), "+f"(d[61]), "+f"(d[62]), "+f"(d[63])
                 : "l"(da), "l"(db), "r"(sd), "n"(TA), "n"(TB));
}
template <int TA, int TB>
__device__ __forceinline__ void wgmma_ss_n160(float* d, uint64_t da, uint64_t db, int sd) {
    asm volatile("{\n.reg .pred p;\nsetp.ne.b32 p, %82, 0;\n"
                 "wgmma.mma_async.sync.aligned.m64n160k16.f32.bf16.bf16 {%0, %1, %2, %3, %4, %5, %6, %7, %8, %9, %10, %11, %12, %13, %14, %15, %16, %17, %18, %19, %20, %21, %22, %23, %24, %25, %26, %27, %28, %29, %30, %31, %32, %33, %34, %35, %36, %37, %38, %39, %40, %41, %42, %43, %44, %45, %46, %47, %48, %49, %50, %51, %52, %53, %54, %55, %56, %57, %58, %59, %60, %61, %62, %63, %64, %65, %66, %67, %68, %69, %70, %71, %72, %73, %74, %75, %76, %77, %78, %79}, %80, %81, p, 1, 1, %83, %84;\n}\n"
                 : "+f"(d[0]), "+f"(d[1]), "+f"(d[2]), "+f"(d[3]), "+f"(d[4]), "+f"(d[5]), "+f"(d[6]), "+f"(d[7]), "+f"(d[8]), "+f"(d[9]), "+f"(d[10]), "+f"(d[11]), "+f"(d[12]), "+f"(d[13]), "+f"(d[14]), "+f"(d[15]), "+f"(d[16]), "+f"(d[17]), "+f"(d[18]), "+f"(d[19]), "+f"(d[20]), "+f"(d[21]), "+f"(d[22]), "+f"(d[23]), "+f"(d[24]), "+f"(d[25]), "+f"(d[26]), "+f"(d[27]), "+f"(d[28]), "+f"(d[29]), "+f"(d[30]), "+f"(d[31]), "+f"(d[32]), "+f"(d[33]), "+f"(d[34]), "+f"(d[35]), "+f"(d[36]), "+f"(d[37]), "+f"(d[38]), "+f"(d[39]), "+f"(d[40]), "+f"(d[41]), "+f"(d[42]), "+f"(d[43]), "+f"(d[44]), "+f"(d[45]), "+f"(d[46]), "+f"(d[47]), "+f"(d[48]), "+f"(d[49]), "+f"(d[50]), "+f"(d[51]), "+f"(d[52]), "+f"(d[53]), "+f"(d[54]), "+f"(d[55]), "+f"(d[56]), "+f"(d[57]), "+f"(d[58]), "+f"(d[59]), "+f"(d[60]), "+f"(d[61]), "+f"(d[62]), "+f"(d[63]), "+f"(d[64]), "+f"(d[65]), "+f"(d[66]), "+f"(d[67]), "+f"(d[68]), "+f"(d[69]), "+f"(d[70]), "+f"(d[71]), "+f"(d[72]), "+f"(d[73]), "+f"(d[74]), "+f"(d[75]), "+f"(d[76]), "+f"(d[77]), "+f"(d[78]), "+f"(d[79])
                 : "l"(da), "l"(db), "r"(sd), "n"(TA), "n"(TB));
}
template <int TB>
__device__ __forceinline__ void wgmma_rs_n48(float* d, uint32_t a0, uint32_t a1, uint32_t a2, uint32_t a3, uint64_t db, int sd) {
    asm volatile("{\n.reg .pred p;\nsetp.ne.b32 p, %29, 0;\n"
                 "wgmma.mma_async.sync.aligned.m64n48k16.f32.bf16.bf16 {%0, %1, %2, %3, %4, %5, %6, %7, %8, %9, %10, %11, %12, %13, %14, %15, %16, %17, %18, %19, %20, %21, %22, %23}, {%24, %25, %26, %27}, %28, p, 1, 1, %30;\n}\n"
                 : "+f"(d[0]), "+f"(d[1]), "+f"(d[2]), "+f"(d[3]), "+f"(d[4]), "+f"(d[5]), "+f"(d[6]), "+f"(d[7]), "+f"(d[8]), "+f"(d[9]), "+f"(d[10]), "+f"(d[11]), "+f"(d[12]), "+f"(d[13]), "+f"(d[14]), "+f"(d[15]), "+f"(d[16]), "+f"(d[17]), "+f"(d[18]), "+f"(d[19]), "+f"(d[20]), "+f"(d[21]), "+f"(d[22]), "+f"(d[23])
                 : "r"(a0), "r"(a1), "r"(a2), "r"(a3), "l"(db), "r"(sd), "n"(TB));
}

struct Ctx {
    uint32_t sm;
    uint32_t bar;
    uint32_t bar0;
    uint32_t bar1;
    uint32_t tag;
    int j, c, rank, wg, w, lane;
};
__device__ __forceinline__ uint32_t bar_at(const Ctx& cx, int idx, int owner) { return (owner ? cx.bar1 : cx.bar0) + 8 * idx; }

__device__ __forceinline__ void store_tile(const Params& P, const Ctx& cx, const float* acc, uint32_t stg, int col0, int row0) {
    const int r = cx.lane >> 2, q = cx.lane & 3;
    const int tr = ((2 * r) & 7) + (r >> 2);
    const uint32_t base = stg + tr * 128 + (q & 1) * 8;
#pragma unroll
    for (int b = 0; b < 5; b++) {
#pragma unroll
        for (int jj = 0; jj < 4; jj++) {
            const uint32_t a = base + b * 2048 + (((2 * jj + (q >> 1)) ^ tr) << 4);
            const int n = 4 * (4 * b + jj);
            asm volatile("st.shared.v2.f32 [%0], {%1, %2};" ::"r"(a), "f"(acc[n]), "f"(acc[n + 1]) : "memory");
            asm volatile("st.shared.v2.f32 [%0], {%1, %2};" ::"r"(a + 1024), "f"(acc[n + 2]), "f"(acc[n + 3]) : "memory");
        }
    }
    fence_async_smem();
    __syncwarp();
    if (cx.lane < 5) {
        tma2d_st(&P.out, stg + cx.lane * 2048, col0 + cx.lane * 32, row0);
        bulk_commit();
        asm volatile("cp.async.bulk.wait_group.read 0;" ::: "memory");
    }
    __syncwarp();
}

template <int UNIT>
__device__ __forceinline__ void a_unit(const Ctx& cx, float* acc) {
    constexpr int I0 = UNIT * 20;
    int slot = I0 % 6, phys = (I0 + 2) % 6, ph = (I0 / 6) & 1;
    int pslot = 0;
    const uint64_t da0 = mkdesc(cx.sm + cx.wg * 8192, 16, 1024, 1);
    const uint64_t db0 = UNIT == 0 ? mkdesc(cx.sm + SM_RING, 2048, 512, 2) : mkdesc(cx.sm + SM_RING, 2560, 128, 0);
    constexpr uint32_t KSTEP = UNIT == 0 ? (1024 >> 4) : (5120 >> 4);
    const bool leader = (threadIdx.x & 127) == 0;
    reg_kill<80>(acc);
#pragma unroll 1
    for (int s = 0; s < 20; s++) {
        if (UNIT == 0 && !(s & 1)) mbar_wait(cx.bar + 8 * (AB_XF + (s >> 1)), 0);
        mbar_wait(cx.bar + 8 * (AB_WF + slot), ph);
        const uint64_t da = da0 + (uint32_t)((s >> 1) * 1024 + (s & 1) * 4);
        const uint64_t db = db0 + (uint32_t)(phys * 640);
        wg_fence();
        wgmma_ss_n160<0, UNIT == 0>(acc, da, db, s);
        wgmma_ss_n160<0, UNIT == 0>(acc, da + 2, db + KSTEP, 1);
        wg_commit();
        wg_wait<1>();
        if (s > 0 && leader) {
            const int i = I0 + s - 1;
            if (i + 6 < 60 && (i < 37 || i > 39)) mbar_arrive_cl(bar_at(cx, AB_WE + pslot, pslot & 1));
            if (UNIT == 2 && s == 4) mbar_arrive(cx.bar + 8 * AB_XFREE);
        }
        pslot = slot;
        if (++slot == 6) { slot = 0; ph ^= 1; }
        if (++phys == 6) phys = 0;
    }
    wg_wait<0>();
    reg_fence<80>(acc);
    if (UNIT == 0 && leader) mbar_arrive_cl(bar_at(cx, AB_WE + pslot, pslot & 1));
}

__device__ __forceinline__ void a_consumer(const Params& P, const Ctx& cx) {
    const int r = cx.lane >> 2, q = cx.lane & 3;
    const bool leader = (threadIdx.x & 127) == 0;
    float acc[80];
    uint32_t vp[40];
    a_unit<0>(cx, acc);
    PROF_W(0 + cx.wg);
#pragma unroll
    for (int i = 0; i < 40; i++) vp[i] = pack_bf16(acc[2 * i], acc[2 * i + 1]);
    a_unit<1>(cx, acc);
    PROF_W(2 + cx.wg);
    bar_sync(1, 256);
    {
        const uint32_t stg = cx.sm + A_STG + cx.wg * 16384;
        const uint32_t aphi = stg + q * 2560 + (8 * cx.w + (r ^ (2 * q))) * 16;
        uint32_t av[3];
#pragma unroll
        for (int t = 0; t < 3; t++) {
            const int m = 4 * t + (cx.lane >> 3);
            av[t] = stg + 10240 + m * 512 + (8 * cx.w + ((cx.lane & 7) ^ (2 * (m / 3)))) * 16;
        }
        const uint32_t one_hi = q == 2 ? 0x3f80u : 0u, one_lo = q == 0 ? 0x3f80u : 0u;
#pragma unroll 1
        for (int g = 0; g < 2; g++) {
#pragma unroll
            for (int hh = 0; hh < 2; hh++) {
                float p[20], e[20];
#pragma unroll
                for (int f = 0; f < 20; f++) p[f] = acc[4 * (f >> 1) + 2 * hh + (f & 1)];
                float mx = p[0], mn = p[0];
#pragma unroll
                for (int f = 1; f < 20; f++) { mx = fmaxf(mx, p[f]); mn = fminf(mn, p[f]); }
                float sp = 0.f, sn = 0.f;
#pragma unroll
                for (int f = 0; f < 20; f++) { e[f] = ex2(p[f] - mx); sp += e[f]; p[f] = ex2(mn - p[f]); sn += p[f]; }
                sp = rcp(sp); sn = rcp(sn);
                uint32_t u[20];
#pragma unroll
                for (int f = 0; f < 10; f++) {
                    u[f] = pack_bf16(e[2 * f] * sp, e[2 * f + 1] * sp);
                    u[10 + f] = pack_bf16(p[2 * f] * sn, p[2 * f + 1] * sn);
                }
                if (g + hh > 0) mbar_wait(cx.bar + 8 * (AB_SE + cx.wg), hh ^ 1);
#pragma unroll
                for (int fg = 0; fg < 5; fg++) sts128(aphi + fg * 512, u[4 * fg], u[4 * fg + 1], u[4 * fg + 2], u[4 * fg + 3]);
                const uint32_t b2 = vp[4 + hh], b7 = vp[14 + hh];
                stsm4(av[0], vp[0 + hh], vp[2 + hh], q < 2 ? b2 : one_hi, q < 2 ? one_lo : b2);
                stsm4(av[1], vp[6 + hh], vp[8 + hh], vp[10 + hh], vp[12 + hh]);
                stsm4(av[2], q < 2 ? b7 : one_hi, q < 2 ? one_lo : b7, vp[16 + hh], vp[18 + hh]);
                fence_async_smem();
                __syncwarp();
                if (cx.lane == 0) mbar_arrive(cx.bar + 8 * (AB_SF + cx.wg));
            }
#pragma unroll
            for (int i = 0; i < 40; i++) acc[i] = acc[40 + i];
#pragma unroll
            for (int i = 0; i < 20; i++) vp[i] = vp[20 + i];
        }
    }
    PROF_W(4 + cx.wg);
    a_unit<2>(cx, acc);
    PROF_W(6 + cx.wg);
    if (leader) {
        mbar_arrive(cx.bar + 8 * AB_QDONE);
#pragma unroll
        for (int b = 0; b < 3; b++) mbar_arrive_cl(bar_at(cx, AB_WOE + b, b & 1));
    }
    {
        const int rr = cx.lane & 7;
        const int pos = (rr >> 1) + 4 * (rr & 1);
        const uint32_t ao = cx.sm + A_OWN + cx.wg * 10240 + (2 * cx.w + ((cx.lane >> 3) & 1)) * 128 + pos * 16 + (cx.lane >> 4) * 1024;
#pragma unroll 1
        for (int g = 0; g < 2; g++) {
            float nd[2][24];
#pragma unroll
            for (int pp = 0; pp < 2; pp++) {
                uint32_t up[2][5], un[2][5];
#pragma unroll
                for (int hh = 0; hh < 2; hh++) {
                    float p[10], e[10];
#pragma unroll
                    for (int i = 0; i < 10; i++) p[i] = acc[4 * (5 * pp + (i >> 1)) + 2 * hh + (i & 1)];
                    float mx = p[0], mn = p[0];
#pragma unroll
                    for (int i = 1; i < 10; i++) { mx = fmaxf(mx, p[i]); mn = fminf(mn, p[i]); }
                    mx = fmaxf(mx, __shfl_xor_sync(0xffffffffu, mx, 1));
                    mn = fminf(mn, __shfl_xor_sync(0xffffffffu, mn, 1));
                    float sp = 0.f, sn = 0.f;
#pragma unroll
                    for (int i = 0; i < 10; i++) { e[i] = ex2(p[i] - mx); sp += e[i]; p[i] = ex2(mn - p[i]); sn += p[i]; }
                    sp += __shfl_xor_sync(0xffffffffu, sp, 1);
                    sn += __shfl_xor_sync(0xffffffffu, sn, 1);
                    sp = rcp(sp); sn = rcp(sn);
#pragma unroll
                    for (int i = 0; i < 5; i++) {
                        up[hh][i] = pack_bf16(e[2 * i] * sp, e[2 * i + 1] * sp);
                        un[hh][i] = pack_bf16(p[2 * i] * sn, p[2 * i + 1] * sn);
                    }
                }
                if (pp == 0 && g == 0) { mbar_wait(cx.bar + 8 * AB_KVB, 0); mbar_wait(cx.bar + 8 * AB_QDONE, 0); }
                const uint64_t db = mkdesc(cx.sm + A_KVB + (2 * g + pp) * 7680, 128, 1280, 0);
                reg_fence<5>(up[0]); reg_fence<5>(up[1]); reg_fence<5>(un[0]); reg_fence<5>(un[1]);
                wg_fence();
#pragma unroll
                for (int s = 0; s < 5; s++) wgmma_rs_n48<1>(nd[pp], up[0][s], up[1][s], un[0][s], un[1][s], db + s * 16, s);
                wg_commit();
            }
            wg_wait<0>();
            reg_fence<24>(nd[0]);
            reg_fence<24>(nd[1]);
#pragma unroll
            for (int pp = 0; pp < 2; pp++) {
                uint32_t o[10];
#pragma unroll
                for (int hh = 0; hh < 2; hh++) {
                    const float r0 = rcp(nd[pp][20 + 2 * hh] + 1e-6f), r1 = rcp(nd[pp][21 + 2 * hh] + 1e-6f);
                    const float rm = q < 2 ? r0 : r1;
#pragma unroll
                    for (int jn = 0; jn < 5; jn++) {
                        const float sc = jn < 2 ? r0 : (jn == 2 ? rm : r1);
                        o[2 * jn + hh] = pack_bf16(nd[pp][4 * jn + 2 * hh] * sc, nd[pp][4 * jn + 2 * hh + 1] * sc);
                    }
                }
                const uint32_t a = ao + g * 20480 + pp * 5120;
                stsm4(a, o[0], o[1], o[2], o[3]);
                stsm4(a + 2048, o[4], o[5], o[6], o[7]);
                stsm2(a + 4096, o[8], o[9]);
            }
            fence_async_smem();
            __syncwarp();
            if (cx.lane == 0) mbar_arrive(cx.bar + 8 * (AB_OST + 2 * g + cx.wg));
#pragma unroll
            for (int i = 0; i < 40; i++) acc[i] = acc[40 + i];
        }
        if (leader) mbar_arrive_cl(bar_at(cx, AB_WOE + 3, 1));
        mbar_wait(cx.bar + 8 * (AB_OST + cx.wg), 0);
        mbar_wait(cx.bar + 8 * (AB_OST + 2 + cx.wg), 0);
    }
    PROF_W(8 + cx.wg);
    reg_kill<80>(acc);
#pragma unroll 1
    for (int n = 0; n < 8; n++) {
        const int b = n & 3;
        const uint32_t ob = (n < 2 || n > 5) ? A_OWN + (n & 1) * 20480 : A_OB + (n - 2) * 20480;
        const uint32_t wb = b == 3 ? A_KVB : A_WO + b * 25600;
        if (n >= 2) mbar_wait(cx.bar + 8 * (AB_OF + n - 2), 0);
        mbar_wait(cx.bar + 8 * (AB_WOF + b), n >> 2);
        const uint64_t da = mkdesc(cx.sm + ob + cx.wg * 10240, 1024, 128, 0);
        const uint64_t db = mkdesc(cx.sm + wb, 5120, 512, 2);
        wg_fence();
#pragma unroll
        for (int s = 0; s < 5; s++) wgmma_ss_n160<0, 1>(acc, da + s * 128, db + s * 64, n + s);
        wg_commit();
        wg_wait<1>();
        if (leader && n > 0) {
            if (n <= 4) mbar_arrive_cl(bar_at(cx, AB_WOE + n - 1, (n - 1) & 1));
            if (n <= 2) mbar_arrive(cx.bar + 8 * (AB_OWNFREE + n - 1));
        }
    }
    wg_wait<0>();
    reg_fence<80>(acc);
    PROF_W(10 + cx.wg);
    bar_sync(1, 256);
    store_tile(P, cx, acc, cx.sm + (cx.wg * 4 + cx.w) * 10240, cx.c * 160, cx.j * 128 + cx.wg * 64 + cx.w * 16);
    PROF_W(12 + cx.wg);
    if (cx.j == 0 && cx.c == 0 && threadIdx.x == 0) g_epoch_a = cx.tag + 1;
}

__device__ __forceinline__ void a_aux(const Params& P, const Ctx& cx) {
    const int r = cx.lane >> 2, q = cx.lane & 3;
    const int tid = threadIdx.x & 127;
    {
        uint32_t a[2][9];
#pragma unroll
        for (int h = 0; h < 2; h++) {
            const unsigned short* wp = (const unsigned short*)P.wphi + (8 * cx.c + 2 * cx.w + h) * 400;
#pragma unroll
            for (int dg = 0; dg < 3; dg++)
#pragma unroll
                for (int fg = 0; fg < 3; fg++) {
                    const int d = 8 * dg + 2 * q, f = 8 * fg + r;
                    uint32_t v = 0;
                    if (d < 20 && f < 20) v = (uint32_t)__ldg(wp + d * 20 + f) | ((uint32_t)__ldg(wp + d * 20 + 20 + f) << 16);
                    a[h][3 * dg + fg] = v;
                }
        }
#pragma unroll 1
        for (int mat = 0; mat < 2; mat++) {
            uint32_t b[2][5][3];
#pragma unroll
            for (int h = 0; h < 2; h++)
#pragma unroll
                for (int nb = 0; nb < 5; nb++) {
                    const uint32_t* src = (const uint32_t*)(P.wqkv + (size_t)(40 * cx.j + 8 * nb + r) * 1920 + (mat ? 0 : 640) +
                                                            20 * (8 * cx.c + 2 * cx.w + h)) + q;
                    b[h][nb][0] = __ldg(src);
                    b[h][nb][1] = __ldg(src + 4);
                    b[h][nb][2] = q < 2 ? __ldg(src + 8) : 0u;
                }
#pragma unroll
            for (int h = 0; h < 2; h++) {
                const int hl = 2 * cx.w + h;
                uint32_t off[3];
#pragma unroll
                for (int fg = 0; fg < 3; fg++) {
                    const int f = 8 * fg + r;
                    const int half = f >= 10, i = f - 10 * half;
                    const int col = mat ? 40 * cx.w + 8 * (i >> 1) + 2 * (2 * h + half) + (i & 1)
                                        : 80 * (hl >> 2) + 8 * (f >> 1) + 2 * (hl & 3) + (f & 1);
                    off[fg] = col * 4 + q;
                }
                uint32_t* dst = (uint32_t*)g_wp + (size_t)((mat * 4 + cx.c) * 80 + 5 * cx.j) * 640;
#pragma unroll
                for (int nb = 0; nb < 5; nb++) {
                    float d0[4] = {0.f, 0.f, 0.f, 0.f}, d1[4] = {0.f, 0.f, 0.f, 0.f};
                    asm("mma.sync.aligned.m16n8k16.row.col.f32.bf16.bf16.f32 {%0,%1,%2,%3}, {%4,%5,%6,%7}, {%8,%9}, {%0,%1,%2,%3};"
                        : "+f"(d0[0]), "+f"(d0[1]), "+f"(d0[2]), "+f"(d0[3])
                        : "r"(a[h][0]), "r"(a[h][1]), "r"(a[h][3]), "r"(a[h][4]), "r"(b[h][nb][0]), "r"(b[h][nb][1]));
                    asm("mma.sync.aligned.m16n8k8.row.col.f32.bf16.bf16.f32 {%0,%1,%2,%3}, {%4,%5}, {%6}, {%0,%1,%2,%3};"
                        : "+f"(d0[0]), "+f"(d0[1]), "+f"(d0[2]), "+f"(d0[3])
                        : "r"(a[h][6]), "r"(a[h][7]), "r"(b[h][nb][2]));
                    asm("mma.sync.aligned.m16n8k16.row.col.f32.bf16.bf16.f32 {%0,%1,%2,%3}, {%4,%5,%6,%5}, {%7,%8}, {%0,%1,%2,%3};"
                        : "+f"(d1[0]), "+f"(d1[1]), "+f"(d1[2]), "+f"(d1[3])
                        : "r"(a[h][2]), "r"(0u), "r"(a[h][5]), "r"(b[h][nb][0]), "r"(b[h][nb][1]));
                    asm("mma.sync.aligned.m16n8k8.row.col.f32.bf16.bf16.f32 {%0,%1,%2,%3}, {%4,%5}, {%6}, {%0,%1,%2,%3};"
                        : "+f"(d1[0]), "+f"(d1[1]), "+f"(d1[2]), "+f"(d1[3])
                        : "r"(a[h][8]), "r"(0u), "r"(b[h][nb][2]));
                    const float L = 1.4426950408889634f;
                    dst[nb * 640 + off[0]] = pack_bf16(d0[0] * L, d0[1] * L);
                    dst[nb * 640 + off[1]] = pack_bf16(d0[2] * L, d0[3] * L);
                    if (r < 4) dst[nb * 640 + off[2]] = pack_bf16(d1[0] * L, d1[1] * L);
                }
            }
            bar_sync(4, 128);
            if (tid == 32 * mat) {
                fence_gpu();
                st_flag(&g_wflag[(mat * 4 + cx.c) * 16 + cx.j], cx.tag);
            }
            PROF_W(16 + mat);
        }
    }
    const int par = cx.tag & 1;
    if (tid < 120) g_kv[par ^ 1][(cx.j * 4 + cx.c) * 120 + tid] = make_float4(0.f, 0.f, 0.f, 0.f);
#pragma unroll 1
    for (int g = 0; g < 2; g++) {
        float kv[4][12];
#pragma unroll 1
        for (int t = 0; t < 4; t++) {
            const int sw = t & 1;
            mbar_wait(cx.bar + 8 * (AB_SF + sw), t >> 1);
            const uint32_t stg = cx.sm + A_STG + sw * 16384;
            const uint64_t da = mkdesc(stg, 128, 512, 0), db = mkdesc(stg + 10240, 128, 512, 0);
            wg_fence();
#pragma unroll
            for (int ks = 0; ks < 2; ks++)
#pragma unroll
                for (int h = 0; h < 4; h++) wgmma_ss_n24<1, 1>(kv[h], da + h * 160 + ks * 16, db + h * 96 + ks * 16, t + ks);
            wg_commit();
            wg_wait<0>();
            if (tid == 0) mbar_arrive(cx.bar + 8 * (AB_SE + sw));
        }
        if (g == 1 && tid == 0) {
#pragma unroll
            for (int s = 1; s < 4; s++) mbar_arrive_cl(bar_at(cx, AB_WE + s, s & 1), 2);
        }
#pragma unroll
        for (int h = 0; h < 4; h++) reg_fence<12>(kv[h]);
        float* dst = (float*)g_kv[par] + (8 * cx.c + 4 * g) * 960 + 2 * cx.w * 192 + cx.lane * 2;
#pragma unroll
        for (int hh = 0; hh < 2; hh++) {
            if (2 * cx.w + hh < 5) {
#pragma unroll
                for (int h = 0; h < 4; h++)
#pragma unroll
                    for (int jj = 0; jj < 3; jj++)
                        asm volatile("red.global.add.v2.f32 [%0], {%1, %2};" ::"l"(dst + h * 960 + hh * 192 + jj * 64),
                                     "f"(kv[h][4 * jj + 2 * hh]), "f"(kv[h][4 * jj + 2 * hh + 1]) : "memory");
            }
        }
    }
    PROF_W(18);
    bar_sync(4, 128);
    if (tid == 0) {
        fence_gpu();
        st_flag(&g_kvflag[cx.c * 16 + cx.j], cx.tag);
    }
    poll_flags(&g_kvflag[cx.c * 16 + (cx.lane & 15)], true, cx.tag);
    PROF_W(19);
    mbar_wait(cx.bar + 8 * AB_XFREE, 0);
#pragma unroll
    for (int t = 0; t < 3; t++) {
        const int idx = tid + 128 * t;
        if (idx < 320) {
            const int pair = idx / 80, k = idx - 80 * pair, u = k & 15;
            const int hh = (u >> 2) & 1;
            const int fp = 20 * (u >> 3) + 10 * ((u >> 1) & 1) + 2 * (k >> 4) + (u & 1);
            const float4* src = g_kv[par] + (8 * cx.c + 2 * pair + hh) * 240 + (fp >> 3) * 48 + (fp & 7) * 2;
            uint32_t u0[3][4];
            float z = 0.f;
#pragma unroll
            for (int jj = 0; jj < 3; jj++) {
                const float4 lo = ldcg4(src + jj * 16), hi = ldcg4(src + jj * 16 + 1);
                u0[jj][0] = pack_bf16(lo.x, lo.y); u0[jj][1] = pack_bf16(lo.z, lo.w);
                u0[jj][2] = pack_bf16(hi.x, hi.y); u0[jj][3] = pack_bf16(hi.z, hi.w);
                if (jj == 0) z = lo.x;
                if (jj == 2 && !hh) z = hi.x;
            }
            const uint32_t dst = cx.sm + A_KVB + pair * 7680 + k * 16;
            const uint32_t zz = hh ? pack_bf16(0.f, z) : pack_bf16(z, 0.f);
            const uint32_t d0 = dst + (hh ? 3 : 0) * 1280, dz = dst + (hh ? 0 : 3) * 1280;
            sts128(d0, hh ? u0[1][0] : u0[0][0], hh ? u0[1][1] : u0[0][1], hh ? u0[1][2] : u0[0][2], hh ? u0[1][3] : u0[0][3]);
            sts128(d0 + 1280, hh ? u0[2][0] : u0[1][0], hh ? u0[2][1] : u0[1][1], hh ? u0[2][2] : u0[1][2], hh ? u0[2][3] : u0[1][3]);
            sts128(dz, 0, 0, 0, 0);
            sts128(dz + 1280, 0, 0, 0, 0);
            sts128(dst + 2 * 1280, hh ? 0u : u0[2][0], hh ? 0u : u0[2][1], hh ? u0[0][2] : 0u, hh ? u0[0][3] : 0u);
            sts128(dst + 5 * 1280, zz, zz, zz, zz);
        }
    }
    fence_async_smem();
    __syncwarp();
    if (cx.lane == 0) mbar_arrive(cx.bar + 8 * AB_KVB);
    PROF_W(20);
    if (cx.lane == 0) {
        const int g = cx.w >> 1, mh = cx.w & 1;
        mbar_wait(cx.bar + 8 * (AB_OST + cx.w), 0);
        bulk_st(g_o + (size_t)(cx.j * 8 + cx.c * 2 + g) * 1280 + mh * 640, cx.sm + A_OWN + g * 20480 + mh * 10240, 10240);
        bulk_commit();
        asm volatile("cp.async.bulk.wait_group 0;" ::: "memory");
        st_flag(&g_oflag[cx.j * 16 + g * 8 + cx.c * 2 + mh], cx.tag);
        mbar_arrive(cx.bar + 8 * (AB_OWNFREE + g));
    }
    PROF_T(21 + cx.w);
}

__device__ __forceinline__ void a_producer(const Params& P, const Ctx& cx) {
    const uint32_t peer = cx.rank ? cx.bar0 : cx.bar1;
    if (cx.w == 0) {
        int slot = cx.rank, phys = cx.rank + 2, ph = 1;
#pragma unroll 1
        for (int i = cx.rank; i < 60; i += 2) {
            if (i - cx.rank == 20 || i - cx.rank == 40) {
                poll_flags(&g_wflag[((i >= 40) * 4 + cx.c) * 16 + (cx.lane & 15)], true, cx.tag);
                PROF_T(26 + (i >= 40));
            }
            if (cx.lane == 0) {
                if (i >= 6) mbar_wait(cx.bar + 8 * (AB_WE + slot), ph);
                const uint32_t fb = 8 * (AB_WF + slot), dst = cx.sm + SM_RING + phys * 10240;
                mbar_expect(cx.bar + fb, 10240);
                mbar_expect_cl(peer + fb, 10240);
                if (i < 20) tma3d_mc(dst, &P.wv, 0, i * 32, 40 + 5 * cx.c, cx.bar + fb);
                else bulk_ld_mc(dst, g_wp + (size_t)(((i >= 40) * 4 + cx.c) * 20 + (i % 20)) * 640, 10240, cx.bar + fb);
            }
            __syncwarp();
            slot += 2; phys += 2;
            if (slot >= 6) { slot -= 6; ph ^= 1; }
            if (phys >= 6) phys -= 6;
        }
        if (cx.lane == 0) {
#pragma unroll 1
            for (int n = cx.rank; n < 8; n += 2) {
                const int b = n & 3;
                const int t = n < 5 ? n - 2 : n - 5;
                const int krow = n < 2 ? 160 * cx.c + 80 * n : 160 * (t + (t >= cx.c)) + 80 * (n >= 5);
                mbar_wait(cx.bar + 8 * (AB_WOE + b), n >> 2);
                const uint32_t fb = 8 * (AB_WOF + b);
                mbar_expect(cx.bar + fb, 25600);
                mbar_expect_cl(peer + fb, 25600);
                tma3d_mc(cx.sm + (b == 3 ? A_KVB : A_WO + b * 25600), &P.wo, 0, krow, 5 * cx.c, cx.bar + fb);
            }
        }
    } else if (cx.w == 1) {
        if (cx.lane == 0) mbar_wait(cx.bar + 8 * AB_QDONE, 0);
        __syncwarp();
#pragma unroll 1
        for (int n = 2; n < 8; n++) {
            const int g = n >= 5, t = n - 2 - 3 * g, cc = t + (t >= cx.c);
            poll_flags(&g_oflag[cx.j * 16 + g * 8 + cc * 2 + (cx.lane & 1)], true, cx.tag);
            if (cx.lane == 0) {
                if (n > 5) mbar_wait(cx.bar + 8 * (AB_OWNFREE + n - 6), 0);
                const uint32_t fb = cx.bar + 8 * (AB_OF + n - 2);
                mbar_expect(fb, 20480);
                bulk_ld(cx.sm + (n > 5 ? A_OWN + (n - 6) * 20480 : A_OB + (n - 2) * 20480),
                        g_o + (size_t)(cx.j * 8 + cc * 2 + g) * 1280, 20480, fb);
            }
            __syncwarp();
            PROF_T(28 + n - 2);
        }
    }
}

struct Cx { float re, im; };
__device__ __forceinline__ Cx cmul(Cx a, Cx b) { return {a.re * b.re - a.im * b.im, a.re * b.im + a.im * b.re}; }
__device__ __forceinline__ Cx cfma(Cx a, Cx b, Cx c) {
    return {fmaf(a.re, b.re, fmaf(-a.im, b.im, c.re)), fmaf(a.re, b.im, fmaf(a.im, b.re, c.im))};
}
__device__ __forceinline__ Cx cshfl_up(Cx a, int d) { return {__shfl_up_sync(0xffffffffu, a.re, d), __shfl_up_sync(0xffffffffu, a.im, d)}; }

__device__ __forceinline__ void b_consumer(const Params& P, const Ctx& cx) {
    const int r = cx.lane >> 2, q = cx.lane & 3;
    const bool leader = (threadIdx.x & 127) == 0;
#pragma unroll 1
    for (int m = cx.wg; m < 5; m += 3) {
        const int ch = 128 * m + 32 * cx.c + 8 * cx.w + r;
        Cx lam;
        float m00, m01, m10, m11;
        {
            const float lr = __bfloat162float(P.lre[ch]), li = __bfloat162float(P.lim[ch]);
            const float dt = __bfloat162float(__float2bfloat16(expf(__bfloat162float(P.ldt[ch]))));
            const float mag = expf(dt * lr);
            float sn, cs;
            sincospif(dt * li * 0.3183098861837907f, &sn, &cs);
            const float ar = mag * cs, ai = mag * sn;
            const float inv = 2.f / (lr * lr + li * li);
            const float cr = ((ar - 1.f) * lr + ai * li) * inv, ci = (ai * lr - (ar - 1.f) * li) * inv;
            lam = {ar, -ai};
            m00 = P.swap ? -ci : cr; m01 = P.swap ? cr : -ci;
            m10 = P.swap ? -cr : -ci; m11 = P.swap ? -ci : -cr;
        }
        Cx l32 = lam;
#pragma unroll
        for (int i = 0; i < 5; i++) l32 = cmul(l32, l32);
        const Cx l64 = cmul(l32, l32), l128 = cmul(l64, l64);
        const Cx l256 = cmul(l128, l128), l512 = cmul(l256, l256), l1024 = cmul(l512, l512);
        const Cx one = {1.f, 0.f};
        const Cx pq32 = cmul((q & 1) ? l32 : one, (q & 2) ? l64 : one);
        const Cx pq512 = cmul((q & 1) ? l512 : one, (q & 2) ? l1024 : one);

        float acc[64];
        if (m >= 2) mbar_wait(cx.bar + 8 * (BB_TURN + m - 2), 0);
        const int i0 = m < 2 ? m : 10 * m, di = m < 2 ? 2 : 1;
        const uint64_t da0 = mkdesc(cx.sm + SM_RING, 16, 1024, 1), db0 = mkdesc(cx.sm, 16, 1024, 1);
#pragma unroll 1
        for (int kb = 0; kb < 10; kb++) {
            const int i = i0 + kb * di, slot = i & 7;
            if (m < 2) mbar_wait(cx.bar + 8 * (BB_XF + kb), 0);
            mbar_wait(cx.bar + 8 * (BB_WF + slot), (i >> 3) & 1);
            const uint64_t da = da0 + (uint32_t)(slot * 512), db = db0 + (uint32_t)(kb * 1024);
            wg_fence();
#pragma unroll
            for (int s = 0; s < 4; s++) wgmma_ss_n128<0, 0>(acc, da + 2 * s, db + 2 * s, kb + s);
            wg_commit();
            if (kb == 9 && leader && m < 4) mbar_arrive(cx.bar + 8 * (BB_TURN + (m ? m - 1 : 0)));
            wg_wait<1>();
            if (kb > 0 && leader) {
                const int ip = i - di;
                if (ip < 42) mbar_arrive_cl(bar_at(cx, BB_WE + (ip & 7), ip & 1));
                if (m == 4 && kb >= 3 && (kb & 1)) {
                    const int s = (kb - 3) >> 1;
                    mbar_arrive(cx.bar + 8 * (BB_HE + s), 2);
                    mbar_arrive_cl(bar_at(cx, BB_CE + s, s & 1), 2);
                }
            }
        }
        wg_wait<0>();
        reg_fence<64>(acc);
        if (leader) {
            const int ip = i0 + 9 * di;
            if (ip < 42) mbar_arrive_cl(bar_at(cx, BB_WE + (ip & 7), ip & 1));
            if (m == 4) {
#pragma unroll
                for (int s = 4; s < 6; s++) {
                    mbar_arrive(cx.bar + 8 * (BB_HE + s), 2);
                    mbar_arrive_cl(bar_at(cx, BB_CE + s, s & 1), 2);
                }
            }
        }
        PROF_W(0 + m);
        Cx e = {0.f, 0.f};
#pragma unroll
        for (int t = 0; t < 32; t++) {
            const int ia = 4 * (t >> 1) + (t & 1);
            const float a = acc[ia], b = acc[ia + 2];
            const Cx in = {fmaf(m00, a, m01 * b), fmaf(m10, a, m11 * b)};
            acc[ia] = in.re; acc[ia + 2] = in.im;
            e = cfma(lam, e, in);
        }
        Cx t1 = cshfl_up(e, 1);
        if (q >= 1) e = cfma(l32, t1, e);
        t1 = cshfl_up(e, 2);
        if (q >= 2) e = cfma(l64, t1, e);
        if (q == 3)
            asm volatile("st.relaxed.gpu.global.v4.u32 [%0], {%1, %2, %3, %2};" ::"l"(g_agg + cx.j * 640 + ch),
                         "r"(__float_as_uint(e.re)), "r"(cx.tag), "r"(__float_as_uint(e.im)) : "memory");
        Cx g = cshfl_up(e, 1);
        if (q == 0) g = {0.f, 0.f};
        PROF_W(5 + m);
        {
            Cx ev[4];
            int it = 0;
            while (true) {
                bool ok = true;
#pragma unroll
                for (int u = 0; u < 4; u++) {
                    const int jj = cx.j - 1 - 4 * q - u;
                    uint32_t x = 0, y = cx.tag, z = 0, w = cx.tag;
                    if (jj >= 0)
                        asm volatile("ld.relaxed.gpu.global.v4.u32 {%0, %1, %2, %3}, [%4];" : "=r"(x), "=r"(y), "=r"(z), "=r"(w)
                                     : "l"(g_agg + jj * 640 + ch) : "memory");
                    ok = ok && y == cx.tag && w == cx.tag;
                    ev[u] = {__uint_as_float(x), __uint_as_float(z)};
                }
                if (__all_sync(0xffffffffu, ok)) break;
                if (++it > (1 << 22)) __trap();
            }
            Cx s = cfma(l128, cfma(l128, cfma(l128, ev[3], ev[2]), ev[1]), ev[0]);
            s = cmul(s, pq512);
            s.re += __shfl_xor_sync(0xffffffffu, s.re, 1); s.im += __shfl_xor_sync(0xffffffffu, s.im, 1);
            s.re += __shfl_xor_sync(0xffffffffu, s.re, 2); s.im += __shfl_xor_sync(0xffffffffu, s.im, 2);
            g = cfma(pq32, s, g);
        }
        PROF_W(10 + m);
        uint4* dst = g_h + (size_t)(cx.j * 20 + 4 * m + 2 * (cx.c >> 1)) * 1024 + (4 * (cx.c & 1) + cx.w) * 128 + q * 32 + r;
#pragma unroll
        for (int i = 0; i < 4; i++) {
            float hr[8], hi[8];
#pragma unroll
            for (int t = 0; t < 8; t++) {
                const int ia = 4 * ((8 * i + t) >> 1) + (t & 1);
                g = cfma(lam, g, Cx{acc[ia], acc[ia + 2]});
                hr[t] = g.re; hi[t] = g.im;
            }
            dst[i * 8] = make_uint4(pack_bf16(hr[0], hr[2]), pack_bf16(hr[4], hr[6]), pack_bf16(hr[1], hr[3]), pack_bf16(hr[5], hr[7]));
            dst[1024 + i * 8] = make_uint4(pack_bf16(hi[0], hi[2]), pack_bf16(hi[4], hi[6]), pack_bf16(hi[1], hi[3]), pack_bf16(hi[5], hi[7]));
        }
        bar_arrive(5 + m, 160);
        PROF_W(15 + m);
    }
    if (cx.wg == 1) return;
    const int mt = cx.wg == 2 ? 0 : 1;
    float acc[80];
    {
        const int tr = ((2 * r) & 7) + (r >> 2);
        const __nv_bfloat162* xp = (const __nv_bfloat162*)(P.xbp + (size_t)(cx.j * 128 + mt * 64 + cx.w * 16 + tr) * 640 + cx.c * 160) + q;
        const __nv_bfloat162* dp = (const __nv_bfloat162*)(P.dskip + cx.c * 160) + q;
#pragma unroll
        for (int jn = 0; jn < 20; jn++) {
            const __nv_bfloat162 dv = __ldg(dp + 4 * jn);
            const float2 a = __bfloat1622float2(__hmul2(__ldg(xp + 4 * jn), dv));
            const float2 b = __bfloat1622float2(__hmul2(__ldg(xp + 4 * jn + 8 * 320), dv));
            acc[4 * jn] = a.x; acc[4 * jn + 1] = a.y; acc[4 * jn + 2] = b.x; acc[4 * jn + 3] = b.y;
        }
    }
    PROF_W(20 + mt);
    {
        int slot = 0, ph = 0, pslot = 0;
        const uint64_t da0 = mkdesc(cx.sm + mt * 1024, 2048, 128, 0), db0 = mkdesc(cx.sm + 16384, 16, 1024, 1);
#pragma unroll 1
        for (int kb = 0; kb < 20; kb++) {
            mbar_wait(cx.bar + 8 * (BB_CF + slot), ph);
            mbar_wait(cx.bar + 8 * (BB_HF + slot), ph);
            const uint64_t da = da0 + (uint32_t)(slot * 2304), db = db0 + (uint32_t)(slot * 2304);
            wg_fence();
#pragma unroll
            for (int s = 0; s < 4; s++) wgmma_ss_n160<1, 0>(acc, da + s * 256, db + 2 * s, 1);
            wg_commit();
            wg_wait<1>();
            if (kb > 0 && kb <= 14 && leader) {
                mbar_arrive(cx.bar + 8 * (BB_HE + pslot));
                mbar_arrive_cl(bar_at(cx, BB_CE + pslot, pslot & 1));
            }
            pslot = slot;
            if (++slot == 6) { slot = 0; ph ^= 1; }
        }
    }
    wg_wait<0>();
    reg_fence<80>(acc);
    PROF_W(24 + mt);
    bar_sync(1, 256);
    store_tile(P, cx, acc, cx.sm + (mt * 4 + cx.w) * 10240, 640 + cx.c * 160, cx.j * 128 + mt * 64 + cx.w * 16);
    PROF_W(26 + mt);
    if (cx.j == 15 && cx.c == 0 && threadIdx.x == 0) g_epoch_b = cx.tag + 1;
}

__device__ __forceinline__ void b_producer(const Params& P, const Ctx& cx) {
    const uint32_t peer = cx.rank ? cx.bar0 : cx.bar1;
    if (cx.w == 0) {
        if (cx.lane == 0) {
#pragma unroll 1
            for (int i = cx.rank; i < 50; i += 2) {
                const int slot = i & 7;
                const int m = i < 20 ? (i & 1) : i / 10, kb = i < 20 ? (i >> 1) : i - 10 * m;
                if (i >= 8) mbar_wait(cx.bar + 8 * (BB_WE + slot), ((i >> 3) & 1) ^ 1);
                const uint32_t fb = 8 * (BB_WF + slot);
                mbar_expect(cx.bar + fb, 8192);
                mbar_expect_cl(peer + fb, 8192);
                tma4d_mc(cx.sm + SM_RING + slot * 8192, &P.bm, kb * 64, 0, 0, 16 * m + 4 * cx.c, cx.bar + fb);
            }
            int slot = cx.rank, ph = 0;
            const CUtensorMap* cm = cx.rank ? &P.cim : &P.cre;
#pragma unroll 1
            for (int kb = cx.rank; kb < 20; kb += 2) {
                mbar_wait(cx.bar + 8 * (BB_CE + slot), ph);
                const uint32_t fb = 8 * (BB_CF + slot);
                mbar_expect(cx.bar + fb, 20480);
                mbar_expect_cl(peer + fb, 20480);
                tma2d_mc(cx.sm + slot * 36864 + 16384, cm, (kb >> 1) * 64, 160 * cx.c, cx.bar + fb);
                slot += 2;
                if (slot >= 6) { slot -= 6; ph ^= 1; }
            }
        }
    } else if (cx.w == 1) {
        int slot = 0, ph = 0;
#pragma unroll 1
        for (int kb = 0; kb < 20; kb++) {
            if (cx.lane == 0) mbar_wait(cx.bar + 8 * (BB_HE + slot), ph);
            __syncwarp();
            if (!(kb & 3)) {
                poll_flags(&g_hflag[(cx.j * 5 + (kb >> 2)) * 4 + (cx.lane & 3)], true, cx.tag);
                PROF_T(30 + (kb >> 2));
            }
            if (cx.lane == 0) {
                const uint32_t fb = cx.bar + 8 * (BB_HF + slot);
                mbar_expect(fb, 16384);
                bulk_ld(cx.sm + slot * 36864, g_h + (size_t)(cx.j * 20 + kb) * 1024, 16384, fb);
            }
            __syncwarp();
            if (++slot == 6) { slot = 0; ph ^= 1; }
        }
    } else {
#pragma unroll 1
        for (int m = cx.w - 2; m < 5; m += 2) {
            bar_sync(5 + m, 160);
            if (cx.lane == 0) {
                fence_gpu();
                st_flag(&g_hflag[(cx.j * 5 + m) * 4 + cx.c], cx.tag);
            }
            __syncwarp();
            PROF_T(35 + m);
        }
    }
}

__global__ void __cluster_dims__(2, 1, 1) __launch_bounds__(512, 1) fused_kernel(const __grid_constant__ Params P) {
    extern __shared__ __align__(1024) uint8_t smem[];
    Ctx cx;
    cx.sm = (uint32_t)__cvta_generic_to_shared(smem);
    cx.bar = cx.sm + SM_BAR;
    cx.rank = blockIdx.x & 1;
    cx.wg = __shfl_sync(0xffffffffu, threadIdx.x >> 7, 0);
    cx.w = __shfl_sync(0xffffffffu, (threadIdx.x >> 5) & 3, 0);
    cx.lane = threadIdx.x & 31;
    const int cl = blockIdx.x >> 1;
    const bool isA = cl >= 4 && cl < 36;
    int jp;
    if (isA) { jp = (cl - 4) & 7; cx.c = (cl - 4) >> 3; }
    else if (cl < 4) { jp = 0; cx.c = cl; }
    else { cx.c = (cl - 36) / 7; jp = 1 + (cl - 36) - 7 * cx.c; }
    cx.j = 2 * jp + cx.rank;

    if (cx.wg == 3 && cx.w < 3) {
        const int b = cx.w == 1 ? cx.lane : 10 + cx.lane + 16 * cx.w;
        uint32_t cnt;
        if (isA) cnt = (b >= AB_WE && b < AB_SE) || b == AB_KVB || (b >= AB_WOE && b < AB_OF) || b >= AB_OWNFREE ? 4
                     : (b == AB_XFREE || b == AB_QDONE) ? 2 : 1;
        else cnt = b >= BB_CE ? 4 : ((b >= BB_WE && b <= BB_TURN) || (b >= BB_HE && b < BB_CF)) ? 2 : 1;
        if (cx.w != 1 || b < 10) mbar_init(cx.bar + 8 * b, cnt);
        asm volatile("fence.mbarrier_init.release.cluster;" ::: "memory");
    }
    __syncwarp();
    asm volatile("barrier.cluster.arrive.relaxed.aligned;" ::: "memory");
    if (threadIdx.x == 416) {
#pragma unroll 1
        for (int kb = 0; kb < 10; kb++) {
            const uint32_t fb = cx.bar + 8 * kb;
            mbar_expect(fb, 16384);
            if (isA) tma2d(cx.sm + kb * 16384, &P.xa, kb * 64, cx.j * 128, fb);
            else tma4d(cx.sm + kb * 16384, &P.xb, kb * 64, 0, 4 * cx.j, 0, fb);
        }
    }
    asm volatile("ld.relaxed.gpu.global.u32 %0, [%1];" : "=r"(cx.tag) : "l"(isA ? &g_epoch_a : &g_epoch_b) : "memory");
    cx.bar0 = mapa(cx.bar, 0);
    cx.bar1 = mapa(cx.bar, 1);
    __syncwarp();
    asm volatile("barrier.cluster.wait.aligned;" ::: "memory");

    if (isA) {
        if (cx.wg < 2) { reg_inc<184>(); a_consumer(P, cx); }
        else if (cx.wg == 2) { reg_dec<104>(); a_aux(P, cx); }
        else { reg_dec<40>(); a_producer(P, cx); }
    } else {
        if (cx.wg < 3) { reg_inc<152>(); b_consumer(P, cx); }
        else { reg_dec<56>(); b_producer(P, cx); }
    }
}

typedef CUresult (*EncodeFn)(CUtensorMap*, CUtensorMapDataType, cuuint32_t, void*, const cuuint64_t*, const cuuint64_t*,
                             const cuuint32_t*, const cuuint32_t*, CUtensorMapInterleave, CUtensorMapSwizzle,
                             CUtensorMapL2promotion, CUtensorMapFloatOOBfill);

static void encode(EncodeFn fn, CUtensorMap* m, CUtensorMapDataType dt, int rank, const void* base, const cuuint64_t* dims,
                   const cuuint64_t* strides, const cuuint32_t* box, CUtensorMapSwizzle sw) {
    const cuuint32_t es[5] = {1, 1, 1, 1, 1};
    fn(m, dt, rank, (void*)base, dims, strides, box, es, CU_TENSOR_MAP_INTERLEAVE_NONE, sw, CU_TENSOR_MAP_L2_PROMOTION_L2_128B,
       CU_TENSOR_MAP_FLOAT_OOB_FILL_NONE);
}

extern "C" void kernel_launch(void* const* d_in, const int* in_sizes, int n_in, void* d_out, int out_size) {
    void* fp = nullptr;
    cudaDriverEntryPointQueryResult qr;
    cudaGetDriverEntryPoint("cuTensorMapEncodeTiled", &fp, cudaEnableDefault, &qr);
    EncodeFn fn = (EncodeFn)fp;
    cudaFuncSetAttribute(fused_kernel, cudaFuncAttributeMaxDynamicSharedMemorySize, SM_TOTAL);

    Params P;
    const CUtensorMapDataType BF = CU_TENSOR_MAP_DATA_TYPE_BFLOAT16;
    {
        const cuuint64_t d[2] = {640, 2048}, s[1] = {1280};
        const cuuint32_t b[2] = {64, 128};
        encode(fn, &P.xa, BF, 2, d_in[0], d, s, b, CU_TENSOR_MAP_SWIZZLE_128B);
    }
    {
        const cuuint64_t d[3] = {32, 640, 60}, s[2] = {3840, 64};
        const cuuint32_t b[3] = {32, 32, 5};
        encode(fn, &P.wv, BF, 3, d_in[1], d, s, b, CU_TENSOR_MAP_SWIZZLE_64B);
    }
    {
        const cuuint64_t d[3] = {32, 640, 20}, s[2] = {1280, 64};
        const cuuint32_t b[3] = {32, 80, 5};
        encode(fn, &P.wo, BF, 3, d_in[3], d, s, b, CU_TENSOR_MAP_SWIZZLE_64B);
    }
    {
        const cuuint64_t d[4] = {640, 2, 64, 16}, s[3] = {1280, 32 * 1280, 2 * 1280};
        const cuuint32_t b[4] = {64, 2, 4, 16};
        encode(fn, &P.xb, BF, 4, d_in[4], d, s, b, CU_TENSOR_MAP_SWIZZLE_128B);
    }
    {
        const uintptr_t re = (uintptr_t)d_in[7], im = (uintptr_t)d_in[8];
        P.swap = im < re;
        const cuuint64_t d[4] = {640, 8, 2, 80}, s[3] = {1280, P.swap ? re - im : im - re, 8 * 1280};
        const cuuint32_t b[4] = {64, 8, 2, 4};
        encode(fn, &P.bm, BF, 4, (const void*)(P.swap ? im : re), d, s, b, CU_TENSOR_MAP_SWIZZLE_128B);
    }
    {
        const cuuint64_t d[2] = {640, 640}, s[1] = {1280};
        const cuuint32_t b[2] = {64, 160};
        encode(fn, &P.cre, BF, 2, d_in[9], d, s, b, CU_TENSOR_MAP_SWIZZLE_128B);
        encode(fn, &P.cim, BF, 2, d_in[10], d, s, b, CU_TENSOR_MAP_SWIZZLE_128B);
    }
    {
        const cuuint64_t d[2] = {1280, 2048}, s[1] = {1280 * 4};
        const cuuint32_t b[2] = {32, 16};
        encode(fn, &P.out, CU_TENSOR_MAP_DATA_TYPE_FLOAT32, 2, d_out, d, s, b, CU_TENSOR_MAP_SWIZZLE_128B);
    }
    P.wqkv = (const bf16*)d_in[1];
    P.wphi = (const bf16*)d_in[2];
    P.xbp = (const bf16*)d_in[4];
    P.lre = (const bf16*)d_in[5];
    P.lim = (const bf16*)d_in[6];
    P.ldt = (const bf16*)d_in[11];
    P.dskip = (const bf16*)d_in[12];
    fused_kernel<<<128, 512, SM_TOTAL, cudaStreamPerThread>>>(P);
}
```

```cpp
#include <cuda_runtime.h>
#include <cuda_bf16.h>
#include <cuda.h>
#include <stdint.h>

typedef __nv_bfloat16 bf16;

struct alignas(128) Scratch {
    uint4 o[16 * 8 * 1280];
    uint4 h[16 * 20 * 1024];
    uint4 agg[16 * 640];
    uint4 phi[4 * 960];
    float4 kv[4 * 2560];
    float4 chan[64 * 640];
    uint32_t kvflag[4 * 16 * 8], oflag[16 * 8 * 8], hflag[16 * 5 * 4 * 8];
};
__device__ Scratch g_scratch;
__device__ __align__(128) uint32_t g_epoch = 1;

struct alignas(64) Params {
    CUtensorMap xa, wv, wo, xb, bm, cre, cim, outa, outb, xd;
    const bf16 *wqkv, *wphi, *wop, *bre, *bim, *crep, *cimp, *lre, *lim, *ldt, *dskip;
    Scratch* s;
    uint32_t* epoch;
    int swap;
    unsigned char role[128];
};

#define R_AUX_REGS 72
#define R_EPI_REGS 200
#define HOLD_C 4
#define HOLD_O 3
#define TA0 500
#define PA 500
#define TB0 800
#define PB 250
#define XB0 2
#define TPB 4500
#define TPF 7000
#define CARRY_NS 150

#define PROF_0(i)
#define PROF_T(i)
#define PROF_W(i)
#define PROF_G(i)
#define PROF_DUMP()
#define TRACE(i)
#define TRACE_W(i)

__device__ __forceinline__ uint32_t mapa(uint32_t addr, uint32_t cta) {
    uint32_t r;
    asm("mapa.shared::cluster.u32 %0, %1, %2;" : "=r"(r) : "r"(addr), "r"(cta));
    return r;
}
__device__ __forceinline__ void mbar_wait(uint32_t bar) {
    asm volatile("{\n.reg .pred p;\nWAIT_LOOP:\nmbarrier.try_wait.parity.shared::cta.b64 p, [%0], 0;\n@!p bra WAIT_LOOP;\n}" ::"r"(bar) : "memory");
}
__device__ __forceinline__ void mbar_wait_b(uint32_t bar) {
    asm volatile(
        "{\n.reg .pred p;\n.reg .u32 n;\n"
        "mbarrier.try_wait.parity.shared::cta.b64 p, [%0], 0;\n"
        "@p bra WAIT_DONE;\n"
        "mov.u32 n, 0;\n"
        "WAIT_LOOP:\n"
        "mbarrier.try_wait.parity.shared::cta.b64 p, [%0], 0;\n"
        "@p bra WAIT_DONE;\n"
        "add.u32 n, n, 1;\n"
        "setp.lt.u32 p, n, 0x40000;\n"
        "@p bra WAIT_LOOP;\n"
        "trap;\n"
        "WAIT_DONE:\n}" ::"r"(bar) : "memory");
}
__device__ __forceinline__ void bar_sync(int id, int n) { asm volatile("bar.sync %0, %1;" ::"r"(id), "r"(n) : "memory"); }
__device__ __forceinline__ void bar_arrive(int id, int n) { asm volatile("bar.arrive %0, %1;" ::"r"(id), "r"(n) : "memory"); }
__device__ __forceinline__ void fence_async_smem() { asm volatile("fence.proxy.async.shared::cta;" ::: "memory"); }
__device__ __forceinline__ uint32_t ld_flag(const uint32_t* p) {
    uint32_t v;
    asm volatile("ld.relaxed.gpu.global.u32 %0, [%1];" : "=r"(v) : "l"(p) : "memory");
    return v;
}
__device__ __forceinline__ uint32_t load_tag(const Params& P) { return ld_flag(P.epoch); }
#define ELECT "{\n.reg .pred p;\nelect.sync _|p, 0xffffffff;\n@p "
#define TMA_LD(dim) "cp.async.bulk.tensor." dim ".shared::cluster.global.mbarrier::complete_tx::bytes"
template <int N>
__device__ __forceinline__ void bar_init(uint32_t bar, uint32_t cnt) {
#pragma unroll
    for (int i = 0; i < N; i++) asm volatile("mbarrier.init.shared::cta.b64 [%0], %1;" ::"r"(bar + 8 * i), "r"(cnt) : "memory");
}
__device__ __forceinline__ void bar_init_done() {
    asm volatile("fence.mbarrier_init.release.cluster;\nbarrier.cluster.arrive.relaxed.aligned;" ::: "memory");
}
__device__ __forceinline__ void e_arrive(uint32_t bar) {
    asm volatile(ELECT "mbarrier.arrive.shared::cta.b64 _, [%0];\n}" ::"r"(bar) : "memory");
}
__device__ __forceinline__ void e_arrive_cl(uint32_t bar_cl) {
    asm volatile(ELECT "mbarrier.arrive.shared::cluster.b64 _, [%0];\n}" ::"r"(bar_cl) : "memory");
}
__device__ __forceinline__ void e_arrive_cl2(uint32_t bar_cl) {
    asm volatile(ELECT "mbarrier.arrive.shared::cluster.b64 _, [%0], 2;\n}" ::"r"(bar_cl) : "memory");
}
__device__ __forceinline__ void e_expect(uint32_t bar, uint32_t bytes) {
    asm volatile(ELECT "mbarrier.arrive.expect_tx.shared::cta.b64 _, [%0], %1;\n}" ::"r"(bar), "r"(bytes) : "memory");
}
__device__ __forceinline__ void e_expect_cl(uint32_t bar_cl, uint32_t bytes) {
    asm volatile(ELECT "mbarrier.arrive.expect_tx.shared::cluster.b64 _, [%0], %1;\n}" ::"r"(bar_cl), "r"(bytes) : "memory");
}
__device__ __forceinline__ void e_tma2d(uint32_t dst, const CUtensorMap* m, int c0, int c1, uint32_t bar) {
    asm volatile(ELECT TMA_LD("2d") " [%0], [%1, {%3, %4}], [%2];\n}" ::"r"(dst), "l"(m), "r"(bar), "r"(c0), "r"(c1) : "memory");
}
__device__ __forceinline__ void e_tma3d(uint32_t dst, const CUtensorMap* m, int c0, int c1, int c2, uint32_t bar) {
    asm volatile(ELECT TMA_LD("3d") " [%0], [%1, {%3, %4, %5}], [%2];\n}"
                 ::"r"(dst), "l"(m), "r"(bar), "r"(c0), "r"(c1), "r"(c2) : "memory");
}
__device__ __forceinline__ void e_tma4d(uint32_t dst, const CUtensorMap* m, int c0, int c1, int c2, int c3, uint32_t bar) {
    asm volatile(ELECT TMA_LD("4d") " [%0], [%1, {%3, %4, %5, %6}], [%2];\n}"
                 ::"r"(dst), "l"(m), "r"(bar), "r"(c0), "r"(c1), "r"(c2), "r"(c3) : "memory");
}
__device__ __forceinline__ void e_tma2d_mc(uint32_t dst, const CUtensorMap* m, int c0, int c1, uint32_t bar) {
    asm volatile(ELECT TMA_LD("2d") ".multicast::cluster [%0], [%1, {%3, %4}], [%2], %5;\n}"
                 ::"r"(dst), "l"(m), "r"(bar), "r"(c0), "r"(c1), "h"((uint16_t)3) : "memory");
}
__device__ __forceinline__ void e_tma3d_mc(uint32_t dst, const CUtensorMap* m, int c0, int c1, int c2, uint32_t bar) {
    asm volatile(ELECT TMA_LD("3d") ".multicast::cluster [%0], [%1, {%3, %4, %5}], [%2], %6;\n}"
                 ::"r"(dst), "l"(m), "r"(bar), "r"(c0), "r"(c1), "r"(c2), "h"((uint16_t)3) : "memory");
}
__device__ __forceinline__ void e_tma4d_mc(uint32_t dst, const CUtensorMap* m, int c0, int c1, int c2, int c3, uint32_t bar) {
    asm volatile(ELECT TMA_LD("4d") ".multicast::cluster [%0], [%1, {%3, %4, %5, %6}], [%2], %7;\n}"
                 ::"r"(dst), "l"(m), "r"(bar), "r"(c0), "r"(c1), "r"(c2), "r"(c3), "h"((uint16_t)3) : "memory");
}
__device__ __forceinline__ void e_bulk_ld(uint32_t dst, const void* src, uint32_t bytes, uint32_t bar) {
    asm volatile(ELECT "cp.async.bulk.shared::cluster.global.mbarrier::complete_tx::bytes [%0], [%1], %2, [%3];\n}"
                 ::"r"(dst), "l"(src), "r"(bytes), "r"(bar) : "memory");
}
__device__ __forceinline__ void e_bulk_st(void* dst, uint32_t src, uint32_t bytes) {
    asm volatile(ELECT "cp.async.bulk.global.shared::cta.bulk_group [%0], [%1], %2;\n}" ::"l"(dst), "r"(src), "r"(bytes) : "memory");
}
__device__ __forceinline__ void e_bulk_add(void* dst, uint32_t src, uint32_t bytes) {
    asm volatile(ELECT "cp.reduce.async.bulk.global.shared::cta.bulk_group.add.f32 [%0], [%1], %2;\n}"
                 ::"l"(dst), "r"(src), "r"(bytes) : "memory");
}
__device__ __forceinline__ void e_tma3d_st(const CUtensorMap* m, uint32_t src, int c0, int c1, int c2) {
    asm volatile(ELECT "cp.async.bulk.tensor.3d.global.shared::cta.bulk_group [%0, {%2, %3, %4}], [%1];\n}"
                 ::"l"(m), "r"(src), "r"(c0), "r"(c1), "r"(c2) : "memory");
}
__device__ __forceinline__ void bulk_commit() { asm volatile("cp.async.bulk.commit_group;" ::: "memory"); }
__device__ __forceinline__ void e_prefetch(const void* src, uint32_t bytes) {
    asm volatile(ELECT "cp.async.bulk.prefetch.L2.global [%0], %1;\n}" ::"l"(src), "r"(bytes) : "memory");
}
__device__ __forceinline__ void e_tma4d_prefetch(const CUtensorMap* m, int c0, int c1, int c2, int c3) {
    asm volatile(ELECT "cp.async.bulk.prefetch.tensor.4d.L2.global [%0, {%1, %2, %3, %4}];\n}"
                 ::"l"(m), "r"(c0), "r"(c1), "r"(c2), "r"(c3) : "memory");
}
__device__ __forceinline__ uint32_t uniform(uint32_t x) {
    uint32_t r;
    asm volatile("shfl.sync.idx.b32 %0, %1, 0, 31, 0xffffffff;" : "=r"(r) : "r"(x));
    return r;
}
__device__ __forceinline__ void e_publish(uint32_t* p, uint32_t tag) {
    asm volatile(ELECT "st.release.gpu.global.u32 [%0], %1;\n}" ::"l"(p), "r"(tag) : "memory");
}
__device__ __forceinline__ uint4 ld_packet(const uint4* p) {
    uint4 v;
    asm volatile("{\n.reg .b128 v;\nld.relaxed.gpu.global.b128 v, [%4];\nmov.b128 {%0, %1, %2, %3}, v;\n}"
                 : "=r"(v.x), "=r"(v.y), "=r"(v.z), "=r"(v.w) : "l"(p) : "memory");
    return v;
}
__device__ __forceinline__ void st_packet_if(bool pred, uint4* p, uint32_t x, uint32_t y, uint32_t z, uint32_t tag) {
    asm volatile("{\n.reg .pred p;\n.reg .b128 v;\nsetp.ne.u32 p, %5, 0;\nmov.b128 v, {%1, %2, %3, %4};\n@p st.relaxed.gpu.global.b128 [%0], v;\n}"
                 ::"l"(p), "r"(x), "r"(y), "r"(z), "r"(tag), "r"((uint32_t)pred) : "memory");
}
__device__ __forceinline__ void ld_packet_if(bool pred, uint4& v, const uint4* p) {
    asm volatile("{\n.reg .pred p;\n.reg .b128 v;\nsetp.ne.u32 p, %5, 0;\nmov.b128 v, {%0, %1, %2, %3};\n"
                 "@p ld.relaxed.gpu.global.b128 v, [%4];\nmov.b128 {%0, %1, %2, %3}, v;\n}"
                 : "+r"(v.x), "+r"(v.y), "+r"(v.z), "+r"(v.w) : "l"(p), "r"((uint32_t)pred) : "memory");
}
__device__ __forceinline__ void wg_fence() { asm volatile("wgmma.fence.sync.aligned;" ::: "memory"); }
__device__ __forceinline__ void wg_commit() { asm volatile("wgmma.commit_group.sync.aligned;" ::: "memory"); }
template <int N> __device__ __forceinline__ void wg_wait() { asm volatile("wgmma.wait_group.sync.aligned %0;" ::"n"(N) : "memory"); }
template <int N> __device__ __forceinline__ void reg_fence(float* d) {
#pragma unroll
    for (int i = 0; i < N; i++) asm volatile("" : "+f"(d[i])::"memory");
}
template <int N> __device__ __forceinline__ void reg_fence(uint32_t* d) {
#pragma unroll
    for (int i = 0; i < N; i++) asm volatile("" : "+r"(d[i])::"memory");
}
template <class T> __device__ __forceinline__ void reg_fence_ptr(T*& p) { asm volatile("" : "+l"(p)::"memory"); }
template <int N> __device__ __forceinline__ void reg_kill(float* d) {
#pragma unroll
    for (int i = 0; i < N; i++) asm volatile("" : "=f"(d[i])::"memory");
}
__device__ __forceinline__ uint32_t desc_lo(uint32_t addr, uint32_t lbo) { return ((addr & 0x3FFFF) >> 4) | ((lbo >> 4) << 16); }
__device__ __forceinline__ uint64_t desc64(uint32_t lo, uint32_t hi) { return ((uint64_t)hi << 32) | lo; }
constexpr uint32_t desc_hi(uint32_t sbo, uint32_t sw) { return (sbo >> 4) | (sw << 30); }
constexpr uint32_t HI_SW128 = desc_hi(1024, 1), HI_SW64 = desc_hi(512, 2), HI_SW64T = desc_hi(1024, 2), HI_128 = desc_hi(128, 0), HI_512 = desc_hi(512, 0),
                   HI_768 = desc_hi(768, 0), HI_1280 = desc_hi(1280, 0);
__device__ __forceinline__ uint32_t pack_bf16(float lo, float hi) {
    uint32_t r;
    asm("cvt.rn.bf16x2.f32 %0, %1, %2;" : "=r"(r) : "f"(hi), "f"(lo));
    return r;
}
__device__ __forceinline__ float ex2(float x) { float r; asm("ex2.approx.ftz.f32 %0, %1;" : "=f"(r) : "f"(x)); return r; }
__device__ __forceinline__ float rcp(float x) { float r; asm("rcp.approx.ftz.f32 %0, %1;" : "=f"(r) : "f"(x)); return r; }
__device__ __forceinline__ void sts128(uint32_t a, uint32_t x, uint32_t y, uint32_t z, uint32_t w) {
    asm volatile("st.shared.v4.u32 [%0], {%1, %2, %3, %4};" ::"r"(a), "r"(x), "r"(y), "r"(z), "r"(w) : "memory");
}
__device__ __forceinline__ void sts32(uint32_t a, uint32_t x) { asm volatile("st.shared.u32 [%0], %1;" ::"r"(a), "r"(x) : "memory"); }
__device__ __forceinline__ void stsm4(uint32_t a, uint32_t x, uint32_t y, uint32_t z, uint32_t w) {
    asm volatile("stmatrix.sync.aligned.m8n8.x4.shared.b16 [%0], {%1, %2, %3, %4};" ::"r"(a), "r"(x), "r"(y), "r"(z), "r"(w) : "memory");
}
__device__ __forceinline__ void stsm2(uint32_t a, uint32_t x, uint32_t y) {
    asm volatile("stmatrix.sync.aligned.m8n8.x2.shared.b16 [%0], {%1, %2};" ::"r"(a), "r"(x), "r"(y) : "memory");
}
__device__ __forceinline__ float4 ld_f4(const float4* p) {
    float4 v;
    asm volatile("ld.global.v4.f32 {%0, %1, %2, %3}, [%4];" : "=f"(v.x), "=f"(v.y), "=f"(v.z), "=f"(v.w) : "l"(p) : "memory");
    return v;
}
__device__ __forceinline__ void poll_flags(const uint32_t* p, uint32_t tag) {
#pragma unroll 1
    for (int it = 0; !__all_sync(0xffffffffu, ld_flag(p) == tag); it++)
        if (it > (1 << 22)) __trap();
}
__device__ __forceinline__ void ldsm4(uint32_t a, uint32_t* d) {
    asm volatile("ldmatrix.sync.aligned.m8n8.x4.shared.b16 {%0, %1, %2, %3}, [%4];"
                 : "=r"(d[0]), "=r"(d[1]), "=r"(d[2]), "=r"(d[3]) : "r"(a) : "memory");
}
__device__ __forceinline__ void cluster_arrive() { asm volatile("barrier.cluster.arrive.relaxed.aligned;" ::: "memory"); }
__device__ __forceinline__ void cluster_wait() { asm volatile("barrier.cluster.wait.aligned;" ::: "memory"); }
__device__ __forceinline__ uint32_t clk32() { uint32_t t; asm volatile("mov.u32 %0, %clock;" : "=r"(t)); return t; }
__device__ __forceinline__ void pace(uint32_t t0, uint32_t t) { while (clk32() - t0 < t) {} }
template <int N> __device__ __forceinline__ void reg_inc() { asm volatile("setmaxnreg.inc.sync.aligned.u32 %0;" ::"n"(N)); }
template <int N> __device__ __forceinline__ void reg_dec() { asm volatile("setmaxnreg.dec.sync.aligned.u32 %0;" ::"n"(N)); }

template <int TA, int TB>
__device__ __forceinline__ void wgmma_ss_n24(float* d, uint64_t da, uint64_t db, int sd) {
    asm volatile("{\n.reg .pred p;\nsetp.ne.b32 p, %14, 0;\n"
                 "wgmma.mma_async.sync.aligned.m64n24k16.f32.bf16.bf16 {%0, %1, %2, %3, %4, %5, %6, %7, %8, %9, %10, %11}, %12, %13, p, 1, 1, %15, %16;\n}\n"
                 : "+f"(d[0]), "+f"(d[1]), "+f"(d[2]), "+f"(d[3]), "+f"(d[4]), "+f"(d[5]), "+f"(d[6]), "+f"(d[7]), "+f"(d[8]), "+f"(d[9]), "+f"(d[10]), "+f"(d[11])
                 : "l"(da), "l"(db), "r"(sd), "n"(TA), "n"(TB));
}
template <int TA, int TB>
__device__ __forceinline__ void wgmma_ss_n128(float* d, uint64_t da, uint64_t db, int sd) {
    asm volatile("{\n.reg .pred p;\nsetp.ne.b32 p, %66, 0;\n"
                 "wgmma.mma_async.sync.aligned.m64n128k16.f32.bf16.bf16 {%0, %1, %2, %3, %4, %5, %6, %7, %8, %9, %10, %11, %12, %13, %14, %15, %16, %17, %18, %19, %20, %21, %22, %23, %24, %25, %26, %27, %28, %29, %30, %31, %32, %33, %34, %35, %36, %37, %38, %39, %40, %41, %42, %43, %44, %45, %46, %47, %48, %49, %50, %51, %52, %53, %54, %55, %56, %57, %58, %59, %60, %61, %62, %63}, %64, %65, p, 1, 1, %67, %68;\n}\n"
                 : "+f"(d[0]), "+f"(d[1]), "+f"(d[2]), "+f"(d[3]), "+f"(d[4]), "+f"(d[5]), "+f"(d[6]), "+f"(d[7]), "+f"(d[8]), "+f"(d[9]), "+f"(d[10]), "+f"(d[11]), "+f"(d[12]), "+f"(d[13]), "+f"(d[14]), "+f"(d[15]), "+f"(d[16]), "+f"(d[17]), "+f"(d[18]), "+f"(d[19]), "+f"(d[20]), "+f"(d[21]), "+f"(d[22]), "+f"(d[23]), "+f"(d[24]), "+f"(d[25]), "+f"(d[26]), "+f"(d[27]), "+f"(d[28]), "+f"(d[29]), "+f"(d[30]), "+f"(d[31]), "+f"(d[32]), "+f"(d[33]), "+f"(d[34]), "+f"(d[35]), "+f"(d[36]), "+f"(d[37]), "+f"(d[38]), "+f"(d[39]), "+f"(d[40]), "+f"(d[41]), "+f"(d[42]), "+f"(d[43]), "+f"(d[44]), "+f"(d[45]), "+f"(d[46]), "+f"(d[47]), "+f"(d[48]), "+f"(d[49]), "+f"(d[50]), "+f"(d[51]), "+f"(d[52]), "+f"(d[53]), "+f"(d[54]), "+f"(d[55]), "+f"(d[56]), "+f"(d[57]), "+f"(d[58]), "+f"(d[59]), "+f"(d[60]), "+f"(d[61]), "+f"(d[62]), "+f"(d[63])
                 : "l"(da), "l"(db), "r"(sd), "n"(TA), "n"(TB));
}
template <int TA, int TB>
__device__ __forceinline__ void wgmma_ss_n160(float* d, uint64_t da, uint64_t db, int sd) {
    asm volatile("{\n.reg .pred p;\nsetp.ne.b32 p, %82, 0;\n"
                 "wgmma.mma_async.sync.aligned.m64n160k16.f32.bf16.bf16 {%0, %1, %2, %3, %4, %5, %6, %7, %8, %9, %10, %11, %12, %13, %14, %15, %16, %17, %18, %19, %20, %21, %22, %23, %24, %25, %26, %27, %28, %29, %30, %31, %32, %33, %34, %35, %36, %37, %38, %39, %40, %41, %42, %43, %44, %45, %46, %47, %48, %49, %50, %51, %52, %53, %54, %55, %56, %57, %58, %59, %60, %61, %62, %63, %64, %65, %66, %67, %68, %69, %70, %71, %72, %73, %74, %75, %76, %77, %78, %79}, %80, %81, p, 1, 1, %83, %84;\n}\n"
                 : "+f"(d[0]), "+f"(d[1]), "+f"(d[2]), "+f"(d[3]), "+f"(d[4]), "+f"(d[5]), "+f"(d[6]), "+f"(d[7]), "+f"(d[8]), "+f"(d[9]), "+f"(d[10]), "+f"(d[11]), "+f"(d[12]), "+f"(d[13]), "+f"(d[14]), "+f"(d[15]), "+f"(d[16]), "+f"(d[17]), "+f"(d[18]), "+f"(d[19]), "+f"(d[20]), "+f"(d[21]), "+f"(d[22]), "+f"(d[23]), "+f"(d[24]), "+f"(d[25]), "+f"(d[26]), "+f"(d[27]), "+f"(d[28]), "+f"(d[29]), "+f"(d[30]), "+f"(d[31]), "+f"(d[32]), "+f"(d[33]), "+f"(d[34]), "+f"(d[35]), "+f"(d[36]), "+f"(d[37]), "+f"(d[38]), "+f"(d[39]), "+f"(d[40]), "+f"(d[41]), "+f"(d[42]), "+f"(d[43]), "+f"(d[44]), "+f"(d[45]), "+f"(d[46]), "+f"(d[47]), "+f"(d[48]), "+f"(d[49]), "+f"(d[50]), "+f"(d[51]), "+f"(d[52]), "+f"(d[53]), "+f"(d[54]), "+f"(d[55]), "+f"(d[56]), "+f"(d[57]), "+f"(d[58]), "+f"(d[59]), "+f"(d[60]), "+f"(d[61]), "+f"(d[62]), "+f"(d[63]), "+f"(d[64]), "+f"(d[65]), "+f"(d[66]), "+f"(d[67]), "+f"(d[68]), "+f"(d[69]), "+f"(d[70]), "+f"(d[71]), "+f"(d[72]), "+f"(d[73]), "+f"(d[74]), "+f"(d[75]), "+f"(d[76]), "+f"(d[77]), "+f"(d[78]), "+f"(d[79])
                 : "l"(da), "l"(db), "r"(sd), "n"(TA), "n"(TB));
}
template <int TB>
__device__ __forceinline__ void wgmma_rs_n40(float* d, uint32_t a0, uint32_t a1, uint32_t a2, uint32_t a3, uint64_t db, int sd) {
    asm volatile("{\n.reg .pred p;\nsetp.ne.b32 p, %25, 0;\n"
                 "wgmma.mma_async.sync.aligned.m64n40k16.f32.bf16.bf16 {%0, %1, %2, %3, %4, %5, %6, %7, %8, %9, %10, %11, %12, %13, %14, %15, %16, %17, %18, %19}, {%20, %21, %22, %23}, %24, p, 1, 1, %26;\n}\n"
                 : "+f"(d[0]), "+f"(d[1]), "+f"(d[2]), "+f"(d[3]), "+f"(d[4]), "+f"(d[5]), "+f"(d[6]), "+f"(d[7]), "+f"(d[8]), "+f"(d[9]), "+f"(d[10]), "+f"(d[11]), "+f"(d[12]), "+f"(d[13]), "+f"(d[14]), "+f"(d[15]), "+f"(d[16]), "+f"(d[17]), "+f"(d[18]), "+f"(d[19])
                 : "r"(a0), "r"(a1), "r"(a2), "r"(a3), "l"(db), "r"(sd), "n"(TB));
}
template <int TB>
__device__ __forceinline__ void wgmma_rs_n48(float* d, uint32_t a0, uint32_t a1, uint32_t a2, uint32_t a3, uint64_t db, int sd) {
    asm volatile("{\n.reg .pred p;\nsetp.ne.b32 p, %29, 0;\n"
                 "wgmma.mma_async.sync.aligned.m64n48k16.f32.bf16.bf16 {%0, %1, %2, %3, %4, %5, %6, %7, %8, %9, %10, %11, %12, %13, %14, %15, %16, %17, %18, %19, %20, %21, %22, %23}, {%24, %25, %26, %27}, %28, p, 1, 1, %30;\n}\n"
                 : "+f"(d[0]), "+f"(d[1]), "+f"(d[2]), "+f"(d[3]), "+f"(d[4]), "+f"(d[5]), "+f"(d[6]), "+f"(d[7]), "+f"(d[8]), "+f"(d[9]), "+f"(d[10]), "+f"(d[11]), "+f"(d[12]), "+f"(d[13]), "+f"(d[14]), "+f"(d[15]), "+f"(d[16]), "+f"(d[17]), "+f"(d[18]), "+f"(d[19]), "+f"(d[20]), "+f"(d[21]), "+f"(d[22]), "+f"(d[23])
                 : "r"(a0), "r"(a1), "r"(a2), "r"(a3), "l"(db), "r"(sd), "n"(TB));
}
template <int TB>
__device__ __forceinline__ void wgmma_rs_n80(float* d, uint32_t a0, uint32_t a1, uint32_t a2, uint32_t a3, uint64_t db, int sd) {
    asm volatile("{\n.reg .pred p;\nsetp.ne.b32 p, %45, 0;\n"
                 "wgmma.mma_async.sync.aligned.m64n80k16.f32.bf16.bf16 {%0, %1, %2, %3, %4, %5, %6, %7, %8, %9, %10, %11, %12, %13, %14, %15, %16, %17, %18, %19, %20, %21, %22, %23, %24, %25, %26, %27, %28, %29, %30, %31, %32, %33, %34, %35, %36, %37, %38, %39}, {%40, %41, %42, %43}, %44, p, 1, 1, %46;\n}\n"
                 : "+f"(d[0]), "+f"(d[1]), "+f"(d[2]), "+f"(d[3]), "+f"(d[4]), "+f"(d[5]), "+f"(d[6]), "+f"(d[7]), "+f"(d[8]), "+f"(d[9]), "+f"(d[10]), "+f"(d[11]), "+f"(d[12]), "+f"(d[13]), "+f"(d[14]), "+f"(d[15]), "+f"(d[16]), "+f"(d[17]), "+f"(d[18]), "+f"(d[19]), "+f"(d[20]), "+f"(d[21]), "+f"(d[22]), "+f"(d[23]), "+f"(d[24]), "+f"(d[25]), "+f"(d[26]), "+f"(d[27]), "+f"(d[28]), "+f"(d[29]), "+f"(d[30]), "+f"(d[31]), "+f"(d[32]), "+f"(d[33]), "+f"(d[34]), "+f"(d[35]), "+f"(d[36]), "+f"(d[37]), "+f"(d[38]), "+f"(d[39])
                 : "r"(a0), "r"(a1), "r"(a2), "r"(a3), "l"(db), "r"(sd), "n"(TB));
}

constexpr uint32_t SM_RING = 163840;
constexpr uint32_t KV_SLOT = 57344;
constexpr uint32_t SLOT = 36864;
constexpr uint32_t SM_BAR = 230912;
constexpr uint32_t SM_TOTAL = 232448;
constexpr uint32_t P_STG = 2 * SLOT, P_PART = 208 * 1024, P_PART_STEP = 24 * 1024, P_PHI = 200 * 1024;
constexpr uint32_t R_OB = 0, R_OWN = 80 * 1024, R_WO = 120 * 1024, R_PHI = 180 * 1024, R_KVB = 195 * 1024;
constexpr unsigned long long BAR_COUNTS_P = 0xF877707773000000ull, BAR_COUNTS_R = 0xF877703333000000ull;
enum { B_XF = 0, B_LATE = 10, RB_WE0 = 11, B_WF = 12, PB_XD = 38, PB_RX = 40, RB_OF = 40, RB_PHI = 46, B_F2 = 48, RB_WOF = 58,
       B_LEAD = 72, PB_PHI = 75, PB_STGDONE = 74, PB_SF = 77, PB_RFREE = 81,
       RB_KVB = 91, RB_TURN = 75, RB_OST = 80, RB_P1 = 84,
       B_WE = 95,
       B_E2 = 132, RB_QDONE = 161, RB_CONST = 162,
       RB_OWNFREE = 168, RB_WOE = 180 };

struct Ctx {
    uint32_t sm;
    uint32_t bar;
    uint32_t barw;
    int wr;
    int j, c, rank, wg, w, lane;
};
__device__ __forceinline__ void make_ctx(Ctx& cx, uint32_t sm, int wr_in) {
    cx.sm = uniform(sm);
    const int wr = uniform(wr_in);
    cx.wr = wr;
    cx.bar = cx.sm + SM_BAR;
    cx.w = wr & 3;
    cx.wg = (wr >> 2) & 3;
    cx.j = (wr >> 4) & 15;
    cx.rank = (wr >> 4) & 1;
    cx.c = (wr >> 8) & 3;
    cx.barw = mapa(cx.bar, wr & 1);
    cx.lane = threadIdx.x & 31;
}

template <uint32_t BOX, bool ADD>
__device__ __forceinline__ void store_tile(const Ctx& cx, float* acc, const uint32_t* xv, uint32_t stg, const CUtensorMap* map,
                                           int col0, int row0, int blk0) {
    const int r = cx.lane >> 2, q = cx.lane & 3;
    const int tr = ((2 * r) & 7) + (r >> 2);
    const uint32_t base = stg + tr * 128 + (q & 1) * 8;
#pragma unroll
    for (int b = 0; b < 5; b++) {
#pragma unroll
        for (int jj = 0; jj < 4; jj++) {
            const uint32_t a = base + b * BOX + (((2 * jj + (q >> 1)) ^ tr) << 4);
            const int n = 4 * (4 * b + jj);
            if (ADD) {
                acc[n] += __uint_as_float(xv[n / 2] << 16); acc[n + 1] += __uint_as_float(xv[n / 2] & 0xffff0000u);
                acc[n + 2] += __uint_as_float(xv[n / 2 + 1] << 16); acc[n + 3] += __uint_as_float(xv[n / 2 + 1] & 0xffff0000u);
            }
            asm volatile("st.shared.v2.f32 [%0], {%1, %2};" ::"r"(a), "f"(acc[n]), "f"(acc[n + 1]) : "memory");
            asm volatile("st.shared.v2.f32 [%0], {%1, %2};" ::"r"(a + 1024), "f"(acc[n + 2]), "f"(acc[n + 3]) : "memory");
        }
        fence_async_smem();
        __syncwarp();
        e_tma3d_st(map, stg + b * BOX, col0 + b * 32, row0, blk0);
    }
    bulk_commit();
    asm volatile("cp.async.bulk.wait_group.read 0;" ::: "memory");
}

enum { G_KV, G_Q, G_C };
struct Pipe {
    uint32_t fb;
    uint32_t eb;
    uint32_t ring;
    uint32_t da, db;
};
template <int G>
__device__ __forceinline__ void issue_stage(Pipe& p, float* acc, int sd) {
    const uint64_t da = desc64(p.da + p.ring, G == G_C ? HI_SW64T : HI_SW128);
    const uint64_t db = desc64(p.db + p.ring, G == G_C ? HI_SW128 : HI_SW64);
    mbar_wait(p.fb);
    wg_fence();
#pragma unroll
    for (int s = 0; s < 4; s++) {
        const uint32_t ob = G == G_C ? 2 * s : (s >> 1) * 640 + (s & 1) * 64;
        wgmma_ss_n160<G == G_C, G != G_C>(acc, da + s * (G == G_C ? 128 : 2), db + ob, s ? 1 : sd);
        if (G == G_KV) {
            wgmma_ss_n160<0, 1>(acc + 80, da + s * 2, db + (ob + 1280), s ? 1 : sd);
            if (s == 1) {
                wg_commit();
                wg_wait<1>();
                e_arrive_cl(p.eb);
                p.eb += 8;
                wg_fence();
            }
        }
    }
    wg_commit();
    constexpr uint32_t STEP = (G == G_KV ? KV_SLOT : SLOT) >> 4, WRAP = STEP * (G == G_KV ? 3 : 6);
    p.fb += 8;
    p.ring += STEP;
    if (p.ring == WRAP) p.ring = 0;
}
template <int G>
__device__ __forceinline__ void release_stage(Pipe& p) {
    e_arrive_cl(p.eb);
    p.eb += 8;
}
template <int G>
__device__ __forceinline__ void run_stages(Pipe& p, float* acc, int n) {
    const uint32_t end = p.fb + 8 * n;
#pragma unroll 1
    do {
        issue_stage<G>(p, acc, 1);
        if (G != G_KV) {
            wg_wait<1>();
            release_stage<G>(p);
        }
    } while (p.fb != end);
}

template <int N>
__device__ __forceinline__ void softmax_sums(const float* e, float* rr, float& sp, float& sn) {
    float s0 = 0.f, s1 = 0.f, n0 = 0.f, n1 = 0.f;
#pragma unroll
    for (int k = 0; k < N / 4; k++) {
        const float ab = e[4 * k] * e[4 * k + 1], cd = e[4 * k + 2] * e[4 * k + 3];
        const float r = rcp(ab * cd);
        rr[2 * k] = r * cd; rr[2 * k + 1] = r * ab;
        const float s01 = e[4 * k] + e[4 * k + 1], s23 = e[4 * k + 2] + e[4 * k + 3];
        if (k == 0) { s0 = s01; s1 = s23; n0 = rr[0] * s01; n1 = rr[1] * s23; }
        else { s0 += s01; s1 += s23; n0 = fmaf(rr[2 * k], s01, n0); n1 = fmaf(rr[2 * k + 1], s23, n1); }
    }
    if (N & 2) {
        rr[N / 2 - 1] = rcp(e[N - 2] * e[N - 1]);
        const float s01 = e[N - 2] + e[N - 1];
        s0 += s01; n0 = fmaf(rr[N / 2 - 1], s01, n0);
    }
    sp = s0 + s1; sn = n0 + n1;
}
__device__ __forceinline__ bool softmax_safe(float sp, float sn) { return (sp < 1073741824.f) & (sn < 1073741824.f); }
template <int N, bool SHARED>
__device__ __forceinline__ void softmax_exact(const float* acc, float* e, float* w, float& sp, float& sn) {
    float mx = acc[0], mn = acc[0];
#pragma unroll
    for (int f = 1; f < N; f++) { mx = fmaxf(mx, acc[4 * (f >> 1) + (f & 1)]); mn = fminf(mn, acc[4 * (f >> 1) + (f & 1)]); }
    if (SHARED) {
        mx = fmaxf(mx, __shfl_xor_sync(0xffffffffu, mx, 1));
        mn = fminf(mn, __shfl_xor_sync(0xffffffffu, mn, 1));
    }
    sp = 0.f; sn = 0.f;
#pragma unroll
    for (int f = 0; f < N; f++) {
        e[f] = ex2(acc[4 * (f >> 1) + (f & 1)] - mx); sp += e[f];
        w[f] = ex2(mn - acc[4 * (f >> 1) + (f & 1)]); sn += w[f];
    }
    if (SHARED) {
        sp += __shfl_xor_sync(0xffffffffu, sp, 1);
        sn += __shfl_xor_sync(0xffffffffu, sn, 1);
    }
}

__device__ __forceinline__ void exp_phase(float* lg, float* e) {
    reg_fence<40>(lg);
#pragma unroll
    for (int i = 0; i < 40; i++) e[i] = ex2(lg[i]);
    reg_fence<40>(e);
}
__device__ __forceinline__ uint32_t hmul_lo(uint32_t a, uint32_t b) {
    uint32_t d;
    asm("{\n.reg .b16 l, h;\n.reg .b32 t;\nmov.b32 {l, h}, %2;\nmov.b32 t, {l, l};\nmul.bf16x2 %0, %1, t;\n}" : "=r"(d) : "r"(a), "r"(b));
    return d;
}
__device__ __forceinline__ uint32_t hfma_lo(uint32_t a, uint32_t b, uint32_t c) {
    uint32_t d;
    asm("{\n.reg .b16 l, h;\n.reg .b32 t;\nmov.b32 {l, h}, %2;\nmov.b32 t, {l, l};\nfma.rn.bf16x2 %0, %1, t, %3;\n}" : "=r"(d) : "r"(a), "r"(b), "r"(c));
    return d;
}
__device__ __forceinline__ uint32_t hmul_hi(uint32_t a, uint32_t b) {
    uint32_t d;
    asm("{\n.reg .b16 l, h;\n.reg .b32 t;\nmov.b32 {l, h}, %2;\nmov.b32 t, {h, h};\nmul.bf16x2 %0, %1, t;\n}" : "=r"(d) : "r"(a), "r"(b));
    return d;
}

__device__ __forceinline__ uint32_t scale_log2e(uint32_t w) { return hfma_lo(w, 0x3fb9u, hmul_lo(w, 0xbb2cu)); }

__device__ __forceinline__ void stage_v(const Ctx& cx, const float* acc) {
    const int q = cx.lane & 3;
    const uint32_t stg = cx.sm + P_STG;
    uint32_t av[3];
#pragma unroll
    for (int t = 0; t < 3; t++) {
        const int m = 4 * t + (cx.lane >> 3), hq = m / 3;
        av[t] = stg + cx.wg * 12288 + m * 512 + (8 * cx.w + ((cx.lane & 7) ^ (2 * hq))) * 16;
    }
    const uint32_t one_hi = q == 2 ? 0x3f80u : 0u, one_lo = q == 0 ? 0x3f80u : 0u;
#pragma unroll
    for (int n = 0; n < 4; n++) {
        const float* v = acc + 80 + 40 * (n >> 1) + 2 * (n & 1);
        const uint32_t o = (n >> 1) * 2 * SLOT + (n & 1) * 6144;
        const uint32_t b2 = pack_bf16(v[8], v[9]), b7 = pack_bf16(v[28], v[29]);
        stsm4(av[0] + o, pack_bf16(v[0], v[1]), pack_bf16(v[4], v[5]), q < 2 ? b2 : one_hi, q < 2 ? one_lo : b2);
        stsm4(av[1] + o, pack_bf16(v[12], v[13]), pack_bf16(v[16], v[17]), pack_bf16(v[20], v[21]), pack_bf16(v[24], v[25]));
        stsm4(av[2] + o, q < 2 ? b7 : one_hi, q < 2 ? one_lo : b7, pack_bf16(v[32], v[33]), pack_bf16(v[36], v[37]));
    }
}

__device__ __forceinline__ void k_epilogue(const Ctx& cx, float* acc) {
    const int r = cx.lane >> 2, q = cx.lane & 3;
    const uint32_t stg = cx.sm + P_STG;
    {
        uint32_t kp[40];
#pragma unroll
        for (int i = 0; i < 40; i++) kp[i] = pack_bf16(acc[2 * i], acc[2 * i + 1]);
        reg_fence<40>(kp);
        reg_kill<80>(acc);
        const uint64_t db = desc64(desc_lo(cx.sm + P_PHI, 128), HI_1280);
        wg_fence();
#pragma unroll
        for (int g = 0; g < 2; g++)
#pragma unroll
            for (int s = 0; s < 5; s++) {
                const uint32_t* a = kp + 20 * g + 4 * s;
                wgmma_rs_n80<1>(acc + 40 * g, a[0], a[1], a[2], a[3], db + (g * 800 + s * 16), s);
            }
        wg_commit();
    }
    uint32_t aphi = stg + 24576 + cx.wg * 20480 + q * 2560 + (8 * cx.w + (r ^ (2 * q))) * 16;
    wg_wait<0>();
    reg_fence<80>(acc);
    PROF_W(50 + cx.wg);
#pragma unroll 1
    for (int g = 0; g < 2; g++) {
        bool ok = true;
        float ee[40];
        exp_phase(acc, ee);
#pragma unroll
        for (int hh = 0; hh < 2; hh++) {
            float e[20], rr[10], sp, sn;
#pragma unroll
            for (int f = 0; f < 20; f++) e[f] = ee[4 * (f >> 1) + 2 * hh + (f & 1)];
            softmax_sums<20>(e, rr, sp, sn);
            ok = ok & softmax_safe(sp, sn);
            const float in = rcp(sn);
            const uint32_t ip = pack_bf16(rcp(sp), 0.f);
            uint32_t u[20];
#pragma unroll
            for (int f = 0; f < 10; f += 2) {
                const uint32_t x = pack_bf16(rr[f] * in, rr[f + 1] * in);
                const uint32_t p0 = pack_bf16(e[2 * f], e[2 * f + 1]), p1 = pack_bf16(e[2 * f + 2], e[2 * f + 3]);
                u[f] = hmul_lo(p0, ip); u[f + 1] = hmul_lo(p1, ip);
                u[10 + f] = hmul_lo(p0, x); u[11 + f] = hmul_hi(p1, x);
            }
#pragma unroll
            for (int fg = 0; fg < 5; fg++)
                sts128(aphi + hh * 10240 + fg * 512, u[4 * fg], u[4 * fg + 1], u[4 * fg + 2], u[4 * fg + 3]);
        }
        if (__builtin_expect(!__all_sync(0xffffffffu, ok), 0)) {
#pragma unroll 1
            for (int hh = 0; hh < 2; hh++) {
                float x[20], w[20], a, b;
                softmax_exact<20, false>(acc, x, w, a, b);
                a = rcp(a); b = rcp(b);
                uint32_t u[20];
#pragma unroll
                for (int f = 0; f < 10; f++) {
                    u[f] = pack_bf16(x[2 * f] * a, x[2 * f + 1] * a);
                    u[10 + f] = pack_bf16(w[2 * f + 1] * b, w[2 * f] * b);
                }
#pragma unroll
                for (int fg = 0; fg < 5; fg++)
                    sts128(aphi + hh * 10240 + fg * 512, u[4 * fg], u[4 * fg + 1], u[4 * fg + 2], u[4 * fg + 3]);
#pragma unroll
                for (int i = 0; i < 10; i++) { acc[4 * i] = acc[4 * i + 2]; acc[4 * i + 1] = acc[4 * i + 3]; }
            }
        }
        fence_async_smem();
        __syncwarp();
        e_arrive(cx.bar + 8 * (PB_SF + 2 * g + cx.wg));
        if (g) break;
        PROF_W(52 + cx.wg);
        aphi += 2 * SLOT;
#pragma unroll
        for (int i = 0; i < 40; i++) acc[i] = acc[40 + i];
    }
}

__device__ __forceinline__ void p_consumer(const Params& P, Ctx& cx) {
    const int q = cx.lane & 3;
    int mt = cx.wg;
    float acc[160];
    mbar_wait(cx.bar + 8 * B_LATE);
    reg_inc<200>();
    {
        Pipe p = {cx.bar + 8 * B_WF, cx.barw + 8 * B_WE, 0, desc_lo(cx.sm + mt * 8192, 16), desc_lo(cx.sm + 16384, 2048)};
        reg_kill<160>(acc);
        {
            const uint64_t da = desc64(p.da, HI_SW128), db = desc64(p.db, HI_SW64);
#pragma unroll
            for (int hf = 0; hf < 2; hf++) {
                mbar_wait(hf ? p.fb : cx.bar);
                wg_fence();
#pragma unroll
                for (int s = 0; s < 2; s++) {
                    wgmma_ss_n160<0, 1>(acc, da + (4 * hf + 2 * s), db + (hf * 640 + s * 64), hf + s);
                    wgmma_ss_n160<0, 1>(acc + 80, da + (4 * hf + 2 * s), db + (hf * 640 + s * 64 + 1280), hf + s);
                }
                wg_commit();
            }
            p.fb += 8;
            p.ring = KV_SLOT >> 4;
        }
        run_stages<G_KV>(p, acc, 8);
        if (mt) {
            wg_wait<0>();
            release_stage<G_KV>(p);
            mbar_wait(cx.bar + 8 * B_LEAD);
        }
        {
            const uint64_t da = desc64(p.da, HI_SW128), db = desc64(p.db, HI_SW64);
            mbar_wait(p.fb);
            wg_fence();
#pragma unroll
            for (int kv = 1; kv >= 0; kv--) {
#pragma unroll
                for (int s = 0; s < 4; s++)
                    wgmma_ss_n160<0, 1>(acc + 80 * kv, da + 2 * s, db + ((s >> 1) * 640 + (s & 1) * 64 + kv * 1280), 1);
                wg_commit();
            }
            wg_wait<2>();
            release_stage<G_KV>(p);
            mbar_wait(cx.bar + 8 * PB_PHI);
            wg_wait<1>();
            if (!mt) e_arrive(cx.bar + 8 * B_LEAD);
            mbar_wait(cx.bar + 8 * (B_WE + 8));
            reg_fence<80>(acc + 80);
            stage_v(cx, acc);
        }
        wg_wait<0>();
        e_arrive_cl(cx.barw + 8 * B_E2);
        e_arrive_cl(cx.barw + 8 * (B_E2 + 1));
        reg_fence<80>(acc);
        PROF_W(2 + cx.wg);
        k_epilogue(cx, acc);
    }
    PROF_W(4 + cx.wg);
    make_ctx(cx, cx.sm, cx.wr);
    mt = cx.wg;
    uint32_t dv[20];
    {
        Pipe p = {cx.bar + 8 * B_F2, cx.barw + 8 * (B_E2 + 5), 0, desc_lo(cx.sm + mt * 8192, 512), desc_lo(cx.sm + 16384, 16)};
        reg_kill<80>(acc);
        const uint32_t* dp = (const uint32_t*)(P.dskip + cx.c * 160) + q;
#pragma unroll
        for (int jn = 0; jn < 20; jn++) asm volatile("ld.global.nc.u32 %0, [%1];" : "=r"(dv[jn]) : "l"(dp + 4 * jn));
        mbar_wait(cx.bar + 8 * PB_STGDONE);
        issue_stage<G_C>(p, acc, 0);
        run_stages<G_C>(p, acc, 4);
        p.ring = 0;
        run_stages<G_C>(p, acc, 1);
        p.eb += 8;
        run_stages<G_C>(p, acc, 14 - HOLD_C);
        if (mt) mbar_wait(cx.bar + 8 * (B_LEAD + 1));
        run_stages<G_C>(p, acc, HOLD_C);
        if (!mt) e_arrive(cx.bar + 8 * (B_LEAD + 1));
    }
    cluster_arrive();
    uint32_t xv[40];
    {
        const int rr = cx.lane & 7, row = (cx.w & 1) * 32 + ((cx.lane >> 3) & 1) * 16 + (cx.w >> 1) * 8 + ((2 * rr) & 7) + (rr >> 2);
        const uint32_t xa = cx.sm + (3 + mt) * SLOT + 16384 + row * 64;
        const uint32_t c0 = (((cx.lane >> 4) ^ (row >> 1)) & 3) << 4;
        mbar_wait(cx.bar + 8 * (PB_XD + mt));
#pragma unroll
        for (int t = 0; t < 10; t++) ldsm4(xa + (t >> 1) * 4096 + (c0 ^ ((t & 1) << 5)), xv + 4 * t);
#pragma unroll
        for (int i = 0; i < 40; i++) asm("mul.bf16x2 %0, %0, %1;" : "+r"(xv[i]) : "r"(dv[i >> 1]));
    }
    reg_fence<40>(xv);
    wg_wait<0>();
    reg_fence<80>(acc);
    PROF_W(10 + mt);
    bar_sync(1 + mt, 128);
    store_tile<SLOT, true>(cx, acc, xv, cx.sm + mt * 8192 + cx.w * 2048, &P.outb, 640 + cx.c * 160,
                     16 * mt + 8 * (cx.w >> 1), 4 * cx.j + 2 * (cx.w & 1));
    PROF_W(12 + mt);
    PROF_DUMP();
    PROF_G(63);
    cluster_wait();
}

__device__ __forceinline__ void kv_mma(const Ctx& cx, int g, float (*kv)[12]) {
#pragma unroll
    for (int h = 0; h < 4; h++) reg_kill<12>(kv[h]);
#pragma unroll 1
    for (int t = 0; t < 2; t++) {
        const uint64_t db = desc64(desc_lo(cx.sm + P_STG + g * 2 * SLOT + t * 12288, 128), HI_512);
        const uint64_t da = db + (1536 + t * 512);
        const uint64_t a01 = da + cx.rank * 320, a23 = da + (320 - cx.rank * 320), b01 = db + cx.rank * 192, b23 = db + (192 - cx.rank * 192);
        mbar_wait(cx.bar + 8 * (PB_SF + 2 * g + t));
        wg_fence();
#pragma unroll
        for (int ks = 0; ks < 4; ks++)
#pragma unroll
            for (int h = 0; h < 4; h++)
                wgmma_ss_n24<1, 1>(kv[h], (h < 2 ? a01 : a23) + ((ks >> 1) * 640 + (h & 1) * 160 + (ks & 1) * 16),
                                   (h < 2 ? b01 : b23) + ((ks >> 1) * 384 + (h & 1) * 96 + (ks & 1) * 16), ks ? 1 : t);
        wg_commit();
    }
}
__device__ __forceinline__ void kv_send(const Ctx& cx, int g, float (*kv)[12], const uint32_t* row, uint32_t peer) {
#pragma unroll
    for (int h = 0; h < 4; h++) reg_fence<12>(kv[h]);
    mbar_wait(cx.bar + 8 * (PB_RFREE + g));
#pragma unroll
    for (int hh = 0; hh < 2; hh++) {
        if (2 * cx.w + hh < 5) {
#pragma unroll
            for (int n = 0; n < 4; n++) {
                const float* x = kv[2 + (n >> 1)] + 2 * hh + (n & 1);
                asm volatile("st.async.weak.shared::cluster.mbarrier::complete_tx::bytes.v4.f32 [%0], {%1, %2, %3, %4}, [%5];"
                             ::"r"(peer + row[hh] - g * P_PART_STEP + (n & 1) * 5120 + (n >> 1) * 256), "f"(x[0]), "f"(x[4]),
                             "f"(x[8]), "f"(1.f), "r"(peer + SM_BAR + 8 * (PB_RX + g)) : "memory");
            }
        }
    }
}
__device__ __forceinline__ void kv_merge(const Ctx& cx, int g, float (*kv)[12], const uint32_t* row) {
    mbar_wait(cx.bar + 8 * (PB_RX + g));
    PROF_W(46 + g);
#pragma unroll
    for (int hh = 0; hh < 2; hh++) {
        if (2 * cx.w + hh < 5) {
            const uint32_t a = cx.sm + row[hh] - g * P_PART_STEP;
            float4 y[4];
#pragma unroll
            for (int n = 0; n < 4; n++)
                asm volatile("ld.shared.v4.f32 {%0, %1, %2, %3}, [%4];" : "=f"(y[n].x), "=f"(y[n].y), "=f"(y[n].z), "=f"(y[n].w)
                             : "r"(a + (n & 1) * 5120 + (n >> 1) * 256) : "memory");
#pragma unroll
            for (int n = 0; n < 4; n++) {
                const float* x = kv[n >> 1] + 2 * hh + (n & 1);
                sts128(a + (n & 1) * 5120 + (n >> 1) * 256, __float_as_uint(y[n].x + x[0]), __float_as_uint(y[n].y + x[4]),
                       __float_as_uint(y[n].z + x[8]), __float_as_uint(y[n].w));
            }
        }
    }
    fence_async_smem();
    bar_arrive(2 + g, 160);
    PROF_W(44 + g);
}

__device__ __forceinline__ void p_aux(const Params& P, const Ctx& cx) {
    const int r = cx.lane >> 2, q = cx.lane & 3;
    const int tid = threadIdx.x & 127;
    {
#pragma unroll 1
        for (int k = tid; k < 160; k += 128) {
            const uint2* wp = (const uint2*)(P.wphi + cx.c * 3200 + k * 20);
            const int hq = (k / 20) & 3;
            const uint32_t dst = cx.sm + P_PHI + (k >= 80 ? 12800 - 1280 : 0) + k * 16;
            uint2 w[5];
#pragma unroll
            for (int i = 0; i < 5; i++) w[i] = __ldg(wp + i);
#pragma unroll
            for (int i = 0; i < 10; i++) {
                sts128(dst + i * 1280, 0, 0, 0, 0);
                sts32(dst + i * 1280 + hq * 4, scale_log2e(i & 1 ? w[i >> 1].y : w[i >> 1].x));
            }
        }
        fence_async_smem();
        mbar_wait(cx.bar + 8 * B_LATE);
        e_arrive(cx.bar + 8 * PB_PHI);
    }
    const uint32_t tag = load_tag(P);
    uint32_t* flags = &P.s->kvflag[cx.c * 16 * 8];
    {
        mbar_wait(cx.bar + 8 * (B_WF + 3));
        P.s->kv[cx.c * 2560 + cx.j * 160 + tid] = make_float4(0.f, 0.f, 0.f, 0.f);
        if (tid < 32) P.s->kv[cx.c * 2560 + cx.j * 160 + 128 + tid] = make_float4(0.f, 0.f, 0.f, 0.f);
        if (tid < 60) {
            const int n = 60 * cx.j + tid, pair = n / 240, ng = (n - 240 * pair) / 48, kk = n % 48 - 8 * (pair & 1);
            const uint32_t* wp = (const uint32_t*)P.wphi + (8 * cx.c + 2 * pair) * 200 + min(max(kk, 0), 39) * 10 + ng;
            const uint32_t a = scale_log2e(__ldg(wp)), b = scale_log2e(__ldg(wp + 5));
            const bool lo = kk >= 0 && kk < 20, hi = kk >= 20 && kk < 40;
            P.s->phi[cx.c * 960 + n] = make_uint4(lo ? a : 0, lo ? b : 0, hi ? a : 0, hi ? b : 0);
        }
        if (tid < 8) flags[cx.j * 8 + tid] = 0;
        bar_sync(4, 128);
        if (cx.w == 0) {
            e_publish(flags + cx.j * 8, tag);
            mbar_wait(cx.bar + 8 * (B_WF + 7));
            poll_flags(flags + (cx.lane & 15) * 8, tag);
        }
        bar_sync(4, 128);
    }
    uint32_t row[2];
#pragma unroll
    for (int hh = 0; hh < 2; hh++) {
        const int fp = 16 * cx.w + 8 * hh + r, sign = fp >= 20, f = fp - 20 * sign, fh = f >= 10, i = f - 10 * fh;
        row[hh] = P_PART + (16 * (i >> 1) + 8 * sign + 2 * fh + (i & 1)) * 64 + q * 16;
    }
    const uint32_t peer = mapa(cx.sm, cx.rank ^ 1);
    if (cx.w < 2) e_expect(cx.bar + 8 * (PB_RX + cx.w), 10240);
#pragma unroll 1
    for (int g = 0; g < 2; g++) {
        float kv[4][12];
        kv_mma(cx, g, kv);
        if (g) e_arrive(cx.bar + 8 * PB_STGDONE); else e_arrive_cl(peer + SM_BAR + 8 * PB_RFREE);
        wg_wait<0>();
        if (g) e_arrive_cl(peer + SM_BAR + 8 * (PB_RFREE + 1)); else e_arrive_cl2(cx.barw + 8 * (B_E2 + 2));
        e_arrive_cl2(cx.barw + 8 * (B_E2 + 3 + g));
        PROF_W(54 + g);
        kv_send(cx, g, kv, row, peer);
        kv_merge(cx, g, kv, row);
    }
}

__device__ __forceinline__ void p_producer(const Params& P, const Ctx& cx, uint32_t t0) {
    if (cx.w == 0) {
        uint32_t dst = cx.sm + KV_SLOT;
#pragma unroll 1
        for (int i = 1; i < 10; i++) {
            const uint32_t fb = cx.bar + 8 * (B_WF + i), dw = dst + 16384 + cx.rank * 20480;
            if (i == 1) mbar_wait_b(cx.bar + 8 * B_LATE);
            if (i < 3) pace(t0, TA0 + i * PA);
            else mbar_wait_b(cx.bar + 8 * (B_WE + i - 3));
            e_expect(fb, KV_SLOT);
            e_tma2d(dst, &P.xa, i * 64, cx.j * 128, fb);
            e_tma3d_mc(dw, &P.wv, 0, i * 64, 20 + 20 * cx.rank + 5 * cx.c, fb);
            e_tma3d_mc(dw + 10240, &P.wv, 0, i * 64 + 32, 20 + 20 * cx.rank + 5 * cx.c, fb);
            dst += KV_SLOT;
            if (dst == cx.sm + 3 * KV_SLOT) dst = cx.sm;
        }
        uint32_t slot = 0;
#pragma unroll 1
        for (int kb = 0; kb < 20; kb++) {
            mbar_wait_b(cx.bar + 8 * (B_E2 + kb));
            e_tma2d_mc(cx.sm + slot * SLOT + 16384 + cx.rank * 10240, (kb & 1) ? &P.cim : &P.cre, (kb >> 1) * 64,
                       160 * cx.c + 80 * cx.rank, cx.bar + 8 * (B_F2 + kb));
            if (++slot == 6 || kb == 4) slot = 0;
        }
#pragma unroll 1
        for (int mt = 0; mt < 2; mt++) {
            mbar_wait_b(cx.bar + 8 * (B_E2 + 20 + mt));
            e_expect(cx.bar + 8 * (PB_XD + mt), 20480);
            e_tma4d(cx.sm + (3 + mt) * SLOT + 16384, &P.xd, 0, mt * 16, 4 * cx.j, 5 * cx.c, cx.bar + 8 * (PB_XD + mt));
        }
        mbar_wait_b(cx.bar + 8 * (B_LEAD + 1));
    } else if (cx.w == 1) {
        const uint32_t tag = load_tag(P);
        mbar_wait(cx.bar + 8 * B_LATE);
        mbar_wait(cx.bar + 8 * B_LEAD);
        uint32_t slot = 0, seen = 0;
        const uint32_t* fl = &P.s->hflag[(cx.j * 20 + (cx.lane < 20 ? cx.lane : 0)) * 8];
#pragma unroll 1
        for (int kb = 0; kb < 20; kb++) {
            const uint32_t fb = cx.bar + 8 * (B_F2 + kb);
#pragma unroll 1
            for (int it = 0; ((seen >> (kb & 30)) & 3) != 3; it++) {
                seen = __ballot_sync(0xffffffffu, ld_flag(fl) == tag);
                if (it > (1 << 22)) __trap();
            }
            if (!(kb & 3)) PROF_T(30 + (kb >> 2));
            mbar_wait(cx.bar + 8 * (B_E2 + kb));
            e_expect(fb, SLOT);
            e_bulk_ld(cx.sm + slot * SLOT, P.s->h + (cx.j * 20 + kb) * 1024, 16384, fb);
            if (++slot == 6 || kb == 4) slot = 0;
        }
    } else {
        const int g = cx.w - 2;
        if (g) {
            const int id = cx.j * 4 + cx.c;
            pace(t0, TPF);
#pragma unroll 1
            for (int i = 0; i < 10; i++) e_prefetch(P.wqkv + (id * 10 + i) * 1920, 1280);
            pace(t0, TPF + 1000);
            e_prefetch(P.crep + id * 6400, 12800);
            pace(t0, TPF + 2000);
            e_prefetch(P.cimp + id * 6400, 12800);
            pace(t0, TPF + 3000);
            e_prefetch(P.wop + id * 6400, 12800);
        }
        float4* dst = P.s->kv + cx.c * 2560 + g * 1280 + cx.rank * 640;
        const uint32_t first = (cx.j & 2) * 160, part = cx.sm + P_PART - g * P_PART_STEP;
        bar_sync(2 + g, 160);
        e_bulk_add(dst + first, part + first * 16, 5120);
        e_bulk_add(dst + (320 - first), part + (320 - first) * 16, 5120);
        bulk_commit();
        asm volatile("cp.async.bulk.wait_group 0;" ::: "memory");
        e_arrive_cl2(mapa(cx.bar + 8 * (B_E2 + 10), 0));
        e_arrive_cl2(mapa(cx.bar + 8 * (B_E2 + 10), 1));
        PROF_T(18 + g);
    }
}

struct Cx { float re, im; };
__device__ __forceinline__ Cx cmul(Cx a, Cx b) { return {a.re * b.re - a.im * b.im, a.re * b.im + a.im * b.re}; }
__device__ __forceinline__ Cx csqr(Cx a) { return {fmaf(a.re, a.re, -a.im * a.im), (a.re + a.re) * a.im}; }
__device__ __forceinline__ Cx cfma(Cx a, Cx b, Cx c) {
    return {fmaf(a.re, b.re, fmaf(-a.im, b.im, c.re)), fmaf(a.re, b.im, fmaf(a.im, b.re, c.im))};
}
__device__ __forceinline__ Cx cshfl_up(Cx a, int d) { return {__shfl_up_sync(0xffffffffu, a.re, d), __shfl_up_sync(0xffffffffu, a.im, d)}; }

__device__ __forceinline__ void q_features(float* lg, const float* ee, uint32_t (*up)[5], uint32_t (*un)[5], float* sp) {
    bool ok = true;
#pragma unroll
    for (int t = 0; t < 4; t++) {
        float e[10], rr[5], sn;
#pragma unroll
        for (int f = 0; f < 10; f++) e[f] = ee[20 * (t >> 1) + 4 * (f >> 1) + 2 * (t & 1) + (f & 1)];
        softmax_sums<10>(e, rr, sp[t], sn);
        sp[t] += __shfl_xor_sync(0xffffffffu, sp[t], 1);
        sn += __shfl_xor_sync(0xffffffffu, sn, 1);
        ok = ok & softmax_safe(sp[t], sn);
        const float a = sp[t] * rcp(sn);
#pragma unroll
        for (int i = 0; i < 5; i++) up[t][i] = pack_bf16(e[2 * i], e[2 * i + 1]);
        const uint32_t x0 = pack_bf16(rr[0] * a, rr[1] * a), x1 = pack_bf16(rr[2] * a, rr[3] * a), x2 = pack_bf16(rr[4] * a, 0.f);
        un[t][0] = hmul_lo(up[t][0], x0); un[t][1] = hmul_hi(up[t][1], x0);
        un[t][2] = hmul_lo(up[t][2], x1); un[t][3] = hmul_hi(up[t][3], x1);
        un[t][4] = hmul_lo(up[t][4], x2);
    }
    if (__builtin_expect(!__all_sync(0xffffffffu, ok), 0)) {
#pragma unroll 1
        for (int t = 0; t < 4; t++) {
            float x[10], w[10], s, b;
            softmax_exact<10, true>(lg, x, w, s, b);
            const float a = s * rcp(b);
            sp[0] = sp[1]; sp[1] = sp[2]; sp[2] = sp[3]; sp[3] = s;
#pragma unroll
            for (int i = 0; i < 5; i++) {
                up[0][i] = up[1][i]; up[1][i] = up[2][i]; up[2][i] = up[3][i];
                un[0][i] = un[1][i]; un[1][i] = un[2][i]; un[2][i] = un[3][i];
                up[3][i] = pack_bf16(x[2 * i], x[2 * i + 1]);
                un[3][i] = pack_bf16(w[2 * i + 1] * a, w[2 * i] * a);
#pragma unroll
                for (int k = 0; k < 2; k++) {
                    lg[4 * i + k] = lg[4 * i + 2 + k]; lg[4 * i + 2 + k] = lg[20 + 4 * i + k]; lg[20 + 4 * i + k] = lg[22 + 4 * i + k];
                }
            }
        }
    }
#pragma unroll
    for (int t = 0; t < 4; t++) { sp[t] *= 1e-6f; reg_fence<5>(up[t]); reg_fence<5>(un[t]); }
}
__device__ __forceinline__ void q_numden(const Ctx& cx, int g, float (*nd)[24], const uint32_t (*up)[5], const uint32_t (*un)[5]) {
    const uint64_t db = desc64(desc_lo(cx.sm + R_KVB + g * 15360, 128), HI_1280);
#pragma unroll
    for (int s = 0; s < 5; s++)
#pragma unroll
        for (int pp = 0; pp < 2; pp++)
            wgmma_rs_n48<1>(nd[pp], up[2 * pp][s], up[2 * pp + 1][s], un[2 * pp][s], un[2 * pp + 1][s], db + (pp * 480 + s * 16), s);
    wg_commit();
}
__device__ __forceinline__ void q_finalize(const Ctx& cx, int mt, int g, float (*nd)[24], const float* sp) {
    const int q = cx.lane & 3, rr = cx.lane & 7;
    const uint32_t ao = cx.sm + R_OWN + g * 20480 + mt * 10240 + (2 * cx.w + ((cx.lane >> 3) & 1)) * 128 +
                        ((rr >> 1) + 4 * (rr & 1)) * 16 + (cx.lane >> 4) * 1024;
    reg_fence<24>(nd[0]);
    reg_fence<24>(nd[1]);
#pragma unroll
    for (int pp = 0; pp < 2; pp++) {
        uint32_t o[10];
#pragma unroll
        for (int hh = 0; hh < 2; hh++) {
            const float rm = rcp((q < 2 ? nd[pp][20 + 2 * hh] : nd[pp][21 + 2 * hh]) + sp[2 * pp + hh]);
            const float ro = __shfl_xor_sync(0xffffffffu, rm, 2);
            const float r0 = q < 2 ? rm : ro, r1 = q < 2 ? ro : rm;
#pragma unroll
            for (int jn = 0; jn < 5; jn++) {
                const float sc = jn < 2 ? r0 : (jn == 2 ? rm : r1);
                o[2 * jn + hh] = pack_bf16(nd[pp][4 * jn + 2 * hh] * sc, nd[pp][4 * jn + 2 * hh + 1] * sc);
            }
        }
        stsm4(ao + pp * 5120, o[0], o[1], o[2], o[3]);
        stsm4(ao + pp * 5120 + 2048, o[4], o[5], o[6], o[7]);
        stsm2(ao + pp * 5120 + 4096, o[8], o[9]);
    }
    fence_async_smem();
    __syncwarp();
    e_arrive(cx.bar + 8 * (RB_OST + 2 * g + mt));
}
__device__ __forceinline__ void proj_chunk(const Ctx& cx, int mt, int n, float* acc, int sd) {
    const uint32_t ob = (n < 2 || n > 5) ? R_OWN + (n & 1) * 20480 : R_OB + (n - 2) * 20480;
    const uint64_t da = desc64(desc_lo(cx.sm + ob + mt * 10240, 1024), HI_128);
    const uint64_t db = desc64(desc_lo(cx.sm + R_WO + (n & 3) * 25600, 5120), HI_SW64);
#pragma unroll
    for (int s = 0; s < 5; s++) wgmma_ss_n160<0, 1>(acc, da + s * 128, db + s * 64, s ? 1 : sd);
    wg_commit();
}

__device__ __forceinline__ void kv_load(const Params& P, const Ctx& cx, int g, uint4* v) {
    const uint4* src = (const uint4*)P.s->kv + cx.c * 2560 + g * 1280 + (threadIdx.x & 127);
    const uint4* mid = src + (threadIdx.x & 64) * 5;
#pragma unroll
    for (int i = 0; i < 10; i++) v[i] = ld_packet((i % 5 == 2 ? mid : src) + (i % 5) * 128 + (i % 5 > 2 ? 320 : 0) + (i / 5) * 320);
}
__device__ __forceinline__ void kv_pack(const Params& P, const Ctx& cx, int g, uint4* v, uint32_t* w) {
#pragma unroll 1
    for (int it = 0;; it++) {
        bool ok = true;
#pragma unroll
        for (int i = 0; i < 10; i++) ok = ok & (v[i].w == 0x41000000u);
        if (__all_sync(0xffffffffu, ok)) break;
        if (it > (1 << 20)) __trap();
        kv_load(P, cx, g, v);
    }
#pragma unroll
    for (int i = 0; i < 5; i++) {
        w[3 * i] = pack_bf16(__uint_as_float(v[i].x), __uint_as_float(v[5 + i].x));
        w[3 * i + 1] = pack_bf16(__uint_as_float(v[i].y), __uint_as_float(v[5 + i].y));
        w[3 * i + 2] = pack_bf16(__uint_as_float(v[i].z), __uint_as_float(v[5 + i].z));
    }
    reg_fence<15>(w);
}
__device__ __forceinline__ void kv_scatter(const Ctx& cx, int g, const uint32_t* w) {
    const int tid = threadIdx.x & 127, q = tid & 3, hh = (tid >> 4) & 1;
    const uint32_t row = cx.sm + R_KVB + g * 15360 + (tid >> 2) * 16, up = tid >= 64 ? 6400 : 0;
    const bool p0 = !hh || q >= 2, p2 = hh || q < 2, pz = q == 2 - 2 * hh;
    const uint32_t a = row + hh * 2 * 1280 + q * 4, az = row + (pz ? 5 : (hh ? 0 : 3) + (q >> 1)) * 1280;
#pragma unroll
    for (int i = 0; i < 5; i++) {
        const uint32_t o = i * 512 + (i > 2 ? 6400 : i == 2 ? up : 0);
        sts32(a + o, p0 ? w[3 * i] : 0);
        sts32(a + o + 1280, w[3 * i + 1]);
        sts32(a + o + 2560, p2 ? w[3 * i + 2] : 0);
        const uint32_t zz = pz ? (hh ? w[3 * i] << 16 : w[3 * i + 2]) : 0;
        sts128(az + o, zz, zz, zz, zz);
    }
    fence_async_smem();
    __syncwarp();
    e_arrive(cx.bar + 8 * (RB_KVB + g));
    PROF_W(44 + 13 * g);
}

__device__ __forceinline__ void q_epilogue(const Ctx& cx, int mt, float* acc, uint32_t woe2, uint32_t woe3) {
    float lg[80], e[40], sp[4], sq[4], nd[2][24];
    uint32_t up[4][5], un[4][5];
    {
        uint32_t qp[40];
#pragma unroll
        for (int i = 0; i < 40; i++) qp[i] = pack_bf16(acc[2 * i], acc[2 * i + 1]);
        reg_fence<40>(qp);
        reg_kill<80>(lg);
        const uint64_t db = desc64(desc_lo(cx.sm + R_PHI, 128), HI_768);
        wg_fence();
#pragma unroll
        for (int g = 0; g < 2; g++) {
#pragma unroll
            for (int s = 0; s < 3; s++)
#pragma unroll
                for (int p = 0; p < 2; p++) {
                    const uint32_t* a = qp + 20 * g + 8 * p + 4 * s;
                    wgmma_rs_n40<1>(lg + 40 * g + 20 * p, a[0], a[1], a[2], a[3], db + ((2 * g + p) * 240 + s * 16), s);
                }
            wg_commit();
        }
    }
    wg_wait<1>();
    exp_phase(lg, e);
    q_features(lg, e, up, un, sp);
    if (mt == 0) PROF_W(58);
    mbar_wait(cx.bar + 8 * RB_KVB);
    if (mt == 0) PROF_W(60);
    wg_wait<0>();
    e_arrive_cl(woe2);
    reg_fence<40>(lg + 40);
    reg_kill<24>(nd[0]);
    reg_kill<24>(nd[1]);
    wg_fence();
    q_numden(cx, 0, nd, up, un);
    exp_phase(lg + 40, e);
    mbar_wait(cx.bar + 8 * RB_QDONE);
    wg_wait<0>();
    q_finalize(cx, mt, 0, nd, sp);
    if (mt == 0) PROF_W(61);
    q_features(lg + 40, e, up, un, sq);
    if (mt == 0) PROF_W(59);
    mbar_wait(cx.bar + 8 * (RB_KVB + 1));
    reg_kill<24>(nd[0]);
    reg_kill<24>(nd[1]);
    wg_fence();
    q_numden(cx, 1, nd, up, un);
    wg_wait<0>();
    e_arrive_cl(woe3);
    q_finalize(cx, mt, 1, nd, sq);
}

__device__ __forceinline__ void publish_o(const Params& P, const Ctx& cx, uint32_t tag, int g) {
    uint32_t* fl = &P.s->oflag[(cx.j * 8 + g * 4 + cx.c) * 8];
    uint4* dst = P.s->o + (cx.j * 8 + cx.c * 2 + g) * 1280;
#pragma unroll
    for (int mh = 0; mh < 2; mh++) {
        mbar_wait(cx.bar + 8 * (RB_OST + 2 * g + mh));
        e_bulk_st(dst + mh * 640, cx.sm + R_OWN + g * 20480 + mh * 10240, 10240);
    }
    bulk_commit();
    asm volatile("cp.async.bulk.wait_group 0;" ::: "memory");
    e_arrive(cx.bar + 8 * (RB_OWNFREE + g));
    e_publish(fl, tag);
    PROF_T(46 + g);
}

__device__ __forceinline__ void r_consumer(const Params& P, Ctx& cx) {
    const int r = cx.lane >> 2, q = cx.lane & 3;
    const uint32_t tag = load_tag(P);
    float4* tab = P.s->chan + (cx.j * 4 + cx.c) * 640;
    if (cx.wg) {
        const int n = 20 * (4 * cx.wg - 4 + cx.w) + cx.lane;
        if (cx.lane < 20) {
            const int ch = 128 * (n >> 5) + 32 * cx.c + (n & 31);
            const float lr = __bfloat162float(P.lre[ch]), li = __bfloat162float(P.lim[ch]);
            const float dt = __bfloat162float(__float2bfloat16(expf(__bfloat162float(P.ldt[ch]))));
            const float mag = expf(dt * lr);
            float sn, cs;
            sincospif(dt * li * 0.3183098861837907f, &sn, &cs);
            const float ar = mag * cs, ai = mag * sn;
            const float inv = __fdividef(2.f, lr * lr + li * li);
            const float cr = ((ar - 1.f) * lr + ai * li) * inv, ci = (ai * lr - (ar - 1.f) * li) * inv;
            const Cx lam = {ar, P.swap ? -ai : ai};
            const uint32_t ma = P.swap ? pack_bf16(-ci, cr) : pack_bf16(cr, -ci), mb = P.swap ? pack_bf16(-cr, -ci) : pack_bf16(-ci, -cr);
            Cx l32 = lam;
#pragma unroll
            for (int t = 0; t < 5; t++) l32 = csqr(l32);
            const Cx l64 = csqr(l32), l128 = csqr(l64), l512 = csqr(csqr(l128)), l1024 = csqr(l512);
            tab[n] = make_float4(lam.re, lam.im, __uint_as_float(ma), __uint_as_float(mb));
            tab[160 + n] = make_float4(l32.re, l32.im, l64.re, l64.im);
            tab[320 + n] = make_float4(l128.re, l128.im, 0.f, 0.f);
            tab[480 + n] = make_float4(l512.re, l512.im, l1024.re, l1024.im);
        }
        __threadfence_block();
        __syncwarp();
        mbar_wait(cx.bar + 8 * B_LATE);
        e_arrive(cx.bar + 8 * RB_CONST);
        PROF_W(40);
    }
    tab += 32 * cx.wg + 8 * cx.w + r;
    if (cx.wg == 1 && cx.w == 3 && cx.lane < 8) P.s->oflag[(cx.j * 8 + 4 + cx.c) * 8 + cx.lane] = 0;
    uint4* agg_st = P.s->agg + cx.j * 640 + 128 * cx.wg + 32 * cx.c + 8 * cx.w + r;
    const uint4* agg_ld = agg_st - (1 + 4 * q) * 640;
    const int nprev = cx.j - 4 * q;
    uint4* dst = P.s->h + (cx.j * 20 + 4 * cx.wg + 2 * (cx.c >> 1)) * 1024 + (4 * (cx.c & 1) + cx.w) * 64 + r * 4 + (q ^ (r >> 1));
    if (q == 3) {
        *agg_st = make_uint4(0, 0, 0, 0);
        if (cx.wg < 2) agg_st[384] = make_uint4(0, 0, 0, 0);
    }
    reg_fence_ptr(agg_st); reg_fence_ptr(agg_ld); reg_fence_ptr(dst); reg_fence_ptr(tab);
    mbar_wait(cx.bar + 8 * B_LATE);
    reg_inc<152>();
#pragma unroll 1
    for (int mv = cx.wg; mv < 5; mv += 3) {
        make_ctx(cx, cx.sm, cx.wr);
        const int m = uniform(mv);
        float acc[64];
        float4 tv[4];
        reg_kill<64>(acc);
        {
            const uint32_t da0 = desc_lo(cx.sm + SM_RING, 16);
            const uint64_t db = desc64(desc_lo(cx.sm, 16), HI_SW128);
            const uint32_t fb = cx.bar + 8 * B_WF + 40 * m, eb = cx.barw + 8 * B_WE + 40 * m;
            if (m) mbar_wait(cx.bar + 8 * (RB_TURN + m - 1));
#pragma unroll
            for (int kk = 0; kk < 5; kk++) {
                const uint64_t da = desc64(da0 + ((m + kk) & 3) * 1024, HI_SW128);
                if (m == 0) {
                    mbar_wait(cx.bar + 8 * (B_XF + 2 * kk));
                    mbar_wait(cx.bar + 8 * (B_XF + 2 * kk + 1));
                }
                mbar_wait(fb + 8 * kk);
                wg_fence();
#pragma unroll
                for (int s = 0; s < 8; s++)
                    wgmma_ss_n128<0, 0>(acc, da + (s >> 2) * 512 + 2 * (s & 3), db + kk * 2048 + (s >> 2) * 1024 + 2 * (s & 3), kk + s);
                wg_commit();
                if (kk == 4) e_arrive(cx.bar + 8 * (RB_TURN + m));
                wg_wait<1>();
                if (kk) e_arrive_cl(kk == 1 && m == 0 ? cx.barw + 8 * RB_WE0 : eb + 8 * (kk - 1));
                if (kk == 3) {
                    if (m == 0) mbar_wait(cx.bar + 8 * RB_CONST);
#pragma unroll
                    for (int t = 0; t < 4; t++) tv[t] = ld_f4(tab + 160 * t);
                }
                if (kk >= 2 && m == 4) { e_arrive_cl(cx.barw + 8 * (B_E2 + kk - 2)); e_arrive_cl(cx.barw + 8 * (B_E2 + kk - 2)); }
            }
            wg_wait<0>();
            e_arrive_cl(eb + 32);
            if (m == 4) {
#pragma unroll
                for (int s = 6; s < 12; s++) e_arrive_cl(cx.barw + 8 * (B_E2 + (s >> 1)));
            }
            mbar_wait(cx.bar + 8 * B_XF);
            reg_fence<64>(acc);
        }
        PROF_W(0 + m);
        struct { Cx lam, l32, l64, l128, pq32, pq512; uint32_t ma, mb; } ck;
        {
            const Cx one = {1.f, 0.f}, zero = {0.f, 0.f}, l32 = {tv[1].x, tv[1].y}, l64 = {tv[1].z, tv[1].w};
            ck.lam = {tv[0].x, tv[0].y};
            ck.ma = __float_as_uint(tv[0].z); ck.mb = __float_as_uint(tv[0].w);
            ck.l32 = q >= 1 ? l32 : zero;
            ck.l64 = q >= 2 ? l64 : zero;
            ck.l128 = {tv[2].x, tv[2].y};
            ck.pq32 = cmul((q & 1) ? l32 : one, (q & 2) ? l64 : one);
            ck.pq512 = cmul((q & 1) ? Cx{tv[3].x, tv[3].y} : one, (q & 2) ? Cx{tv[3].z, tv[3].w} : one);
        }
        Cx e = {acc[0], acc[2]};
#pragma unroll
        for (int t = 1; t < 32; t++) e = cfma(ck.lam, e, Cx{acc[4 * (t >> 1) + (t & 1)], acc[4 * (t >> 1) + (t & 1) + 2]});
        e = cfma(ck.l32, cshfl_up(e, 1), e);
        e = cfma(ck.l64, cshfl_up(e, 2), e);
        st_packet_if(q == 3, agg_st, __float_as_uint(e.re), __float_as_uint(e.im), 0u, tag);
        Cx g = cshfl_up(e, 1);
        if (q == 0) g = {0.f, 0.f};
        e_arrive(cx.bar + 8 * (RB_P1 + m));
        PROF_W(5 + m);
        {
            uint4 v[4];
#pragma unroll
            for (int u = 0; u < 4; u++) v[u] = make_uint4(0u, 0u, 0u, tag);
            __nanosleep(CARRY_NS);
#pragma unroll 1
            for (int it = 0;; it++) {
#pragma unroll
                for (int u = 0; u < 4; u++) ld_packet_if(nprev > u, v[u], agg_ld - u * 640);
                if (__all_sync(0xffffffffu, (v[0].w == tag) & (v[1].w == tag) & (v[2].w == tag) & (v[3].w == tag))) break;
                if (it > (1 << 21)) __trap();
                __nanosleep(100);
            }
            Cx ev[4];
#pragma unroll
            for (int u = 0; u < 4; u++) ev[u] = {__uint_as_float(v[u].x), __uint_as_float(v[u].y)};
            Cx s = cfma(ck.l128, cfma(ck.l128, cfma(ck.l128, ev[3], ev[2]), ev[1]), ev[0]);
            s = cmul(s, ck.pq512);
            s.re += __shfl_xor_sync(0xffffffffu, s.re, 1); s.im += __shfl_xor_sync(0xffffffffu, s.im, 1);
            s.re += __shfl_xor_sync(0xffffffffu, s.re, 2); s.im += __shfl_xor_sync(0xffffffffu, s.im, 2);
            g = cfma(ck.pq32, s, g);
        }
        PROF_W(10 + m);
        reg_fence<2>(&g.re);
        if (m < 3) mbar_wait(cx.bar + 8 * (RB_P1 + m + 1));
#pragma unroll
        for (int i = 0; i < 4; i++) {
            float sr[8], si[8];
#pragma unroll
            for (int t = 0; t < 8; t++) {
                const int ia = 4 * ((8 * i + t) >> 1) + (t & 1);
                g = cfma(ck.lam, g, Cx{acc[ia], acc[ia + 2]});
                sr[t] = g.re; si[t] = g.im;
            }
            uint32_t ya[4], yb[4];
#pragma unroll
            for (int k = 0; k < 4; k++) {
                const int t = 4 * (k & 1) + (k >> 1);
                const uint32_t pr = pack_bf16(sr[t], sr[t + 2]), pi = pack_bf16(si[t], si[t + 2]);
                ya[k] = hfma_lo(pr, ck.ma, hmul_hi(pi, ck.ma));
                yb[k] = hfma_lo(pr, ck.mb, hmul_hi(pi, ck.mb));
            }
            dst[(i >> 1) * 512 + (i & 1) * 32] = make_uint4(ya[0], ya[1], ya[2], ya[3]);
            dst[1024 + (i >> 1) * 512 + (i & 1) * 32] = make_uint4(yb[0], yb[1], yb[2], yb[3]);
        }
        tab += 96;
        agg_st += 384; agg_ld += 384; dst += 12 * 1024;
        bar_arrive(5 + m, 160);
        PROF_W(15 + m);
    }
    make_ctx(cx, cx.sm, cx.wr);
    if (cx.wg == 1) {
        reg_dec<R_AUX_REGS>();
        mbar_wait(cx.bar + 8 * B_F2);
#pragma unroll 1
        for (int g = 0; g < 2; g++) {
            uint4 v[10];
            uint32_t w[15];
            if (cx.w == 0) poll_flags((const uint32_t*)(P.s->kv + cx.c * 2560 + g * 1280 + (cx.lane & 3) * 320 + 319) + 3, 0x41000000u);
            bar_sync(4, 128);
            PROF_W(43 + 13 * g);
            kv_load(P, cx, g, v);
            kv_pack(P, cx, g, v, w);
            mbar_wait(cx.bar + 8 * (B_E2 + 11));
            kv_scatter(cx, g, w);
        }
        if (cx.w == 3) publish_o(P, cx, tag, 1);
        return;
    }
    int mt = cx.wg == 2 ? 0 : 1;
    float acc[80];
    {
        Pipe p = {cx.bar + 8 * B_F2, cx.barw + 8 * (B_E2 + 6), 0, desc_lo(cx.sm + mt * 8192, 16), desc_lo(cx.sm + 16384, 2048)};
        reg_kill<80>(acc);
        issue_stage<G_Q>(p, acc, 0);
        run_stages<G_Q>(p, acc, 7);
        if (mt) mbar_wait(cx.bar + 8 * B_LEAD);
        run_stages<G_Q>(p, acc, 2);
        if (!mt) e_arrive(cx.bar + 8 * B_LEAD);
    }
    reg_inc<R_EPI_REGS>();
    mbar_wait(cx.bar + 8 * RB_PHI);
    wg_wait<0>();
    reg_fence<80>(acc);
    PROF_W(20 + mt);
    uint32_t woe0 = mapa(cx.bar + 8 * RB_WOE, 0), woe1 = mapa(cx.bar + 8 * RB_WOE, 1);
    e_arrive(cx.bar + 8 * RB_QDONE);
    e_arrive_cl(woe0);
    e_arrive_cl(woe1 + 8);
    q_epilogue(cx, mt, acc, woe0 + 16, woe1 + 24);
    PROF_W(22 + mt);
    make_ctx(cx, cx.sm, cx.wr);
    mt = cx.wg == 2 ? 0 : 1;
    woe0 = mapa(cx.bar + 8 * RB_WOE, 0); woe1 = mapa(cx.bar + 8 * RB_WOE, 1);
    reg_kill<80>(acc);
    mbar_wait(cx.bar + 8 * (RB_OST + mt));
    mbar_wait(cx.bar + 8 * RB_WOF);
    wg_fence();
    proj_chunk(cx, mt, 0, acc, 0);
#pragma unroll 1
    for (int n = 1; n < 8; n++) {
        mbar_wait(cx.bar + 8 * (n < 2 ? RB_OST + 2 + mt : RB_OF + n - 2));
        mbar_wait(cx.bar + 8 * (RB_WOF + n));
        if (n == 8 - HOLD_O && mt) mbar_wait(cx.bar + 8 * (B_LEAD + 1));
        wg_fence();
        proj_chunk(cx, mt, n, acc, 1);
        wg_wait<1>();
        if (n <= 4) e_arrive_cl(((n & 1) ? woe0 : woe1) + 8 * (n + 3));
        if (n <= 2) e_arrive(cx.bar + 8 * (RB_OWNFREE + n - 1));
    }
    if (!mt) e_arrive(cx.bar + 8 * (B_LEAD + 1));
    cluster_arrive();
    wg_wait<0>();
    reg_fence<80>(acc);
    PROF_W(24 + mt);
    store_tile<2048, false>(cx, acc, nullptr, cx.sm + R_OB + cx.w * 20480 + mt * 10240, &P.outa, cx.c * 160,
                     16 * (cx.w & 1), 4 * cx.j + 2 * mt + (cx.w >> 1));
    PROF_W(26 + mt);
    PROF_DUMP();
    PROF_G(63);
    cluster_wait();
}

__device__ __forceinline__ void r_producer(const Params& P, const Ctx& cx, uint32_t t0) {
    if (cx.w == 0) {
#pragma unroll 1
        for (int i = 2; i < 25; i++) {
            const int slot = i & 3;
            const int m = (i * 13) >> 6, kk = i - 5 * m;
            const uint32_t fb = cx.bar + 8 * (B_WF + i);
            mbar_wait_b(cx.bar + 8 * (i < 4 ? B_LATE : i == 4 ? RB_WE0 : B_WE + i - 4));
            e_expect(fb, 16384);
            e_tma4d_mc(cx.sm + SM_RING + slot * 16384 + cx.rank * 8192, &P.bm, kk * 128 + cx.rank * 64, 0, 0, 16 * m + 4 * cx.c, fb);
        }
#pragma unroll 1
        for (int kb = 0; kb < 10; kb++) {
            const int slot = kb < 6 ? kb : kb - 6;
            mbar_wait_b(cx.bar + 8 * (B_E2 + kb));
            e_tma3d_mc(cx.sm + slot * SLOT + 16384 + cx.rank * 10240, &P.wv, 0, kb * 64 + cx.rank * 32, 5 * cx.c,
                       cx.bar + 8 * (B_F2 + kb));
        }
        const uint32_t peer = mapa(cx.bar, cx.rank ^ 1);
#pragma unroll 1
        for (int n = cx.rank; n < 8; n += 2) {
            const int b = n & 3;
            const int t = n < 5 ? n - 2 : n - 5;
            const int krow = n < 2 ? 160 * cx.c + 80 * n : 160 * (t + (t >= cx.c)) + 80 * (n >= 5);
            const uint32_t fb = 8 * (RB_WOF + n);
            mbar_wait_b(cx.bar + 8 * (RB_WOE + n));
            e_expect(cx.bar + fb, 25600);
            e_expect_cl(peer + fb, 25600);
            e_tma3d_mc(cx.sm + R_WO + b * 25600, &P.wo, 0, krow, 5 * cx.c, cx.bar + fb);
        }
        mbar_wait_b(cx.bar + 8 * (B_LEAD + 1));
    } else if (cx.w == 1) {
#pragma unroll 1
        for (int kb = XB0; kb < 10; kb++) {
            pace(t0, TB0 + kb * PB);
            e_expect(cx.bar + 8 * kb, 16384);
            e_tma4d(cx.sm + kb * 16384, &P.xb, kb * 64, 0, 4 * cx.j, 0, cx.bar + 8 * kb);
            if (kb == 6 && cx.j < 12) e_tma4d_prefetch(&P.bm, (cx.j < 2 ? 8 + cx.j : cx.j - 2) * 64, 0, 0, (cx.j < 2 ? 0 : 16) + 4 * cx.c);
        }
        const int id = cx.j * 4 + cx.c;
        pace(t0, TPB);
        e_prefetch(P.bre + 256 * 640 + id * 3840, 7680);
        e_prefetch(P.bim + 256 * 640 + id * 3840, 7680);
        const uint32_t tag = load_tag(P);
        if (cx.lane < 8) P.s->oflag[(cx.j * 8 + cx.c) * 8 + cx.lane] = 0;
        __syncwarp();
        mbar_wait(cx.bar + 8 * B_LATE);
        mbar_wait(cx.bar + 8 * (RB_TURN + 2));
        poll_flags(&P.s->kvflag[(cx.c * 16 + (cx.lane & 15)) * 8], tag);
#pragma unroll 1
        for (int kb = 0; kb < 10; kb++) {
            const int slot = kb < 6 ? kb : kb - 6;
            const uint32_t fb = cx.bar + 8 * (B_F2 + kb);
            mbar_wait(cx.bar + 8 * (B_E2 + kb));
            e_expect(fb, SLOT);
            e_tma2d(cx.sm + slot * SLOT, &P.xa, kb * 64, cx.j * 128, fb);
        }
        mbar_wait(cx.bar + 8 * (B_E2 + 11));
        e_expect(cx.bar + 8 * RB_PHI, 15360);
        e_bulk_ld(cx.sm + R_PHI, P.s->phi + cx.c * 960, 15360, cx.bar + 8 * RB_PHI);
        publish_o(P, cx, tag, 0);
    } else {
        const int g = cx.w - 2;
        const uint32_t tag = load_tag(P);
        if (2 * (cx.lane >> 3) + g < 5) P.s->hflag[((cx.j * 5 + 2 * (cx.lane >> 3) + g) * 4 + cx.c) * 8 + (cx.lane & 7)] = 0;
        __syncwarp();
#pragma unroll 1
        for (int m = g; m < 5; m += 2) {
            uint32_t* fl = &P.s->hflag[((cx.j * 5 + m) * 4 + cx.c) * 8];
            bar_sync(5 + m, 160);
            e_publish(fl, tag);
            PROF_T(35 + m);
        }
        mbar_wait(cx.bar + 8 * RB_QDONE);
        const uint32_t* fl = &P.s->oflag[(cx.j * 8 + g * 4 + (cx.lane & 3)) * 8];
        int t = 0;
#pragma unroll 1
        for (int it = 0; t < 3; it++) {
            const uint32_t m = __ballot_sync(0xffffffffu, ld_flag(fl) == tag);
#pragma unroll 1
            while (t < 3) {
                const int n = 2 + 3 * g + t, cc = t + (t >= cx.c);
                if (!((m >> cc) & 1)) break;
                if (n > 5) mbar_wait(cx.bar + 8 * (RB_OWNFREE + n - 6));
                const uint32_t fb = cx.bar + 8 * (RB_OF + n - 2);
                e_expect(fb, 20480);
                e_bulk_ld(cx.sm + (n > 5 ? R_OWN + (n - 6) * 20480 : R_OB + (n - 2) * 20480),
                          P.s->o + (cx.j * 8 + cc * 2 + g) * 1280, 20480, fb);
                PROF_T(50 + n - 2);
                t++;
            }
            if (it > (1 << 22)) __trap();
        }
        if (g == 1 && cx.j == 0 && cx.c == 0 && cx.lane == 0) *P.epoch = tag + 1;
    }
}

__global__ void __cluster_dims__(2, 1, 1) __launch_bounds__(512, 1) fused_kernel(const __grid_constant__ Params P) {
    extern __shared__ __align__(1024) uint8_t smem[];
    Ctx cx;
    const uint32_t t0 = clk32();
    const uint32_t sm = (uint32_t)__cvta_generic_to_shared(smem);
    const int warp = __shfl_sync(0xffffffffu, threadIdx.x >> 5, 0);
    const bool isP = blockIdx.x - 8 < 64;

    const uint32_t bar = sm + SM_BAR;
    bar_init<1>(bar + 8 * (warp ^ 13), (warp ^ 13) == B_LATE ? 16 : (warp ^ 13) == RB_WE0 ? 4 : 1);
    bar_init_done();
    const int role = P.role[blockIdx.x];
    if (warp == 13) {
        if (isP) {
            e_expect(bar, 16384 + 20480);
            e_tma2d(sm, &P.xa, 0, (role & 15) * 128, bar);
            cluster_wait();
        } else {
            e_expect(bar, 16384);
            e_tma4d(sm, &P.xb, 0, 0, 4 * (role & 15), 0, bar);
            cluster_wait();
#pragma unroll
            for (int kb = 1; kb < XB0; kb++) {
                e_expect(bar + 8 * kb, 16384);
                e_tma4d(sm + kb * 16384, &P.xb, kb * 64, 0, 4 * (role & 15), 0, bar + 8 * kb);
            }
        }
    } else {
      if (warp == 12) {
        const uint32_t fb = bar + 8 * B_WF;
        const int c = (role >> 4) & 3, rank = role & 1;
        cluster_wait();
        if (isP) {
            e_tma3d_mc(sm + 16384 + rank * 20480, &P.wv, 0, 0, 20 + 20 * rank + 5 * c, bar);
            e_expect(fb, 20480);
            e_tma3d_mc(sm + 16384 + rank * 20480 + 10240, &P.wv, 0, 32, 20 + 20 * rank + 5 * c, fb);
        } else {
            e_expect(fb, 16384);
            e_tma4d_mc(sm + SM_RING + rank * 8192, &P.bm, rank * 64, 0, 0, 4 * c, fb);
            e_expect(fb + 8, 16384);
            e_tma4d_mc(sm + SM_RING + 16384 + rank * 8192, &P.bm, 128 + rank * 64, 0, 0, 4 * c, fb + 8);
        }
        PROF_0(36);
        bar_init<8>(fb + 32, 1);
      } else {
        const int grp = (13 - warp) & 15;
        const uint32_t cnt = (((isP ? BAR_COUNTS_P : BAR_COUNTS_R) >> (4 * grp)) & 15) + 1;
        cluster_wait();
        if (warp == 0) PROF_0(37);
        if (!(((isP ? 0xC604 : 0x0400) >> grp) & 1)) bar_init<12>(bar + 96 * grp, cnt);
      }
      asm volatile("fence.mbarrier_init.release.cluster;" ::: "memory");
    }
    const int wr = warp | (role << 4);
    if (warp >= 12) {
        if (isP) { reg_dec<32>(); e_arrive(bar + 8 * B_LATE); make_ctx(cx, sm, wr); p_producer(P, cx, t0); }
        else { reg_dec<40>(); e_arrive(bar + 8 * B_LATE); make_ctx(cx, sm, wr); r_producer(P, cx, t0); }
    } else if (!isP) {
        e_arrive(bar + 8 * B_LATE); make_ctx(cx, sm, wr); r_consumer(P, cx);
    } else if (warp >= 8) {
        reg_dec<80>(); e_arrive(bar + 8 * B_LATE); make_ctx(cx, sm, wr); p_aux(P, cx);
    } else {
        e_arrive(bar + 8 * B_LATE); make_ctx(cx, sm, wr); p_consumer(P, cx);
    }
}

typedef CUresult (*EncodeFn)(CUtensorMap*, CUtensorMapDataType, cuuint32_t, void*, const cuuint64_t*, const cuuint64_t*,
                             const cuuint32_t*, const cuuint32_t*, CUtensorMapInterleave, CUtensorMapSwizzle,
                             CUtensorMapL2promotion, CUtensorMapFloatOOBfill);

static void encode(EncodeFn fn, CUtensorMap* m, CUtensorMapDataType dt, int rank, const void* base, const cuuint64_t* dims,
                   const cuuint64_t* strides, const cuuint32_t* box, CUtensorMapSwizzle sw) {
    const cuuint32_t es[5] = {1, 1, 1, 1, 1};
    fn(m, dt, rank, (void*)base, dims, strides, box, es, CU_TENSOR_MAP_INTERLEAVE_NONE, sw, CU_TENSOR_MAP_L2_PROMOTION_L2_128B,
       CU_TENSOR_MAP_FLOAT_OOB_FILL_NONE);
}

extern "C" void kernel_launch(void* const* d_in, const int* in_sizes, int n_in, void* d_out, int out_size) {
    void* fp = nullptr;
    cudaDriverEntryPointQueryResult qr;
    cudaGetDriverEntryPoint("cuTensorMapEncodeTiled", &fp, cudaEnableDefault, &qr);
    EncodeFn fn = (EncodeFn)fp;
    cudaFuncSetAttribute(fused_kernel, cudaFuncAttributeMaxDynamicSharedMemorySize, SM_TOTAL);

    Params P;
    const CUtensorMapDataType BF = CU_TENSOR_MAP_DATA_TYPE_BFLOAT16;
    {
        const cuuint64_t d[2] = {640, 2048}, s[1] = {1280};
        const cuuint32_t b[2] = {64, 128};
        encode(fn, &P.xa, BF, 2, d_in[0], d, s, b, CU_TENSOR_MAP_SWIZZLE_128B);
    }
    {
        const cuuint64_t d[3] = {32, 640, 60}, s[2] = {3840, 64};
        const cuuint32_t b[3] = {32, 32, 5};
        encode(fn, &P.wv, BF, 3, d_in[1], d, s, b, CU_TENSOR_MAP_SWIZZLE_64B);
    }
    {
        const cuuint64_t d[3] = {32, 640, 20}, s[2] = {1280, 64};
        const cuuint32_t b[3] = {32, 80, 5};
        encode(fn, &P.wo, BF, 3, d_in[3], d, s, b, CU_TENSOR_MAP_SWIZZLE_64B);
    }
    {
        const cuuint64_t d[4] = {640, 2, 64, 16}, s[3] = {1280, 32 * 1280, 2 * 1280};
        const cuuint32_t b[4] = {64, 2, 4, 16};
        encode(fn, &P.xb, BF, 4, d_in[4], d, s, b, CU_TENSOR_MAP_SWIZZLE_128B);
    }
    {
        const cuuint64_t d[4] = {32, 32, 64, 20}, s[3] = {1280, 32 * 1280, 64};
        const cuuint32_t b[4] = {32, 16, 4, 5};
        encode(fn, &P.xd, BF, 4, d_in[4], d, s, b, CU_TENSOR_MAP_SWIZZLE_64B);
    }
    {
        const uintptr_t re = (uintptr_t)d_in[7], im = (uintptr_t)d_in[8];
        P.swap = im < re;
        const cuuint64_t d[4] = {640, 8, 2, 80}, s[3] = {1280, P.swap ? re - im : im - re, 8 * 1280};
        const cuuint32_t b[4] = {64, 8, 2, 4};
        encode(fn, &P.bm, BF, 4, (const void*)(P.swap ? im : re), d, s, b, CU_TENSOR_MAP_SWIZZLE_128B);
    }
    {
        const cuuint64_t d[2] = {640, 640}, s[1] = {1280};
        const cuuint32_t b[2] = {64, 80};
        encode(fn, &P.cre, BF, 2, d_in[9], d, s, b, CU_TENSOR_MAP_SWIZZLE_128B);
        encode(fn, &P.cim, BF, 2, d_in[10], d, s, b, CU_TENSOR_MAP_SWIZZLE_128B);
    }
    {
        const cuuint64_t d[3] = {1280, 32, 64}, s[2] = {1280 * 4, 32 * 1280 * 4};
        const cuuint32_t ba[3] = {32, 16, 1}, bb[3] = {32, 8, 2};
        encode(fn, &P.outa, CU_TENSOR_MAP_DATA_TYPE_FLOAT32, 3, d_out, d, s, ba, CU_TENSOR_MAP_SWIZZLE_128B);
        encode(fn, &P.outb, CU_TENSOR_MAP_DATA_TYPE_FLOAT32, 3, d_out, d, s, bb, CU_TENSOR_MAP_SWIZZLE_128B);
    }
    cudaGetSymbolAddress((void**)&P.s, g_scratch);
    cudaGetSymbolAddress((void**)&P.epoch, g_epoch);
    P.wqkv = (const bf16*)d_in[1];
    P.wphi = (const bf16*)d_in[2];
    P.wop = (const bf16*)d_in[3];
    P.bre = (const bf16*)d_in[7];
    P.bim = (const bf16*)d_in[8];
    P.crep = (const bf16*)d_in[9];
    P.cimp = (const bf16*)d_in[10];
    P.lre = (const bf16*)d_in[5];
    P.lim = (const bf16*)d_in[6];
    P.ldt = (const bf16*)d_in[11];
    P.dskip = (const bf16*)d_in[12];
    for (int b = 0; b < 128; b++) {
        const int cl = b >> 1;
        int jp, c, a = 0;
        if (cl < 4) { jp = 0; c = cl; }
        else if (cl < 36) { jp = (cl - 4) & 7; c = (cl - 4) >> 3; a = 64; }
        else { c = (cl - 36) / 7; jp = 1 + (cl - 36) - 7 * c; }
        P.role[b] = (unsigned char)(a | (c << 4) | (2 * jp + (b & 1)));
    }
    fused_kernel<<<128, 512, SM_TOTAL, cudaStreamPerThread>>>(P);
}
```
